```python
import torch

def _softmax(x, axis=-1):
    return torch.softmax(x, dim=axis)

def _gelu(x):
    return torch.nn.functional.gelu(x, approximate='tanh')

def _silu(x):
    return torch.nn.functional.silu(x)

def _sigmoid(x):
    return torch.sigmoid(x)

def _layernorm(x, axis=-1, eps=1e-05):
    m = x.mean(dim=axis, keepdim=True)
    v = x.var(dim=axis, keepdim=True, unbiased=False)
    return (x - m) / torch.sqrt(v + eps)

def _scatter_add(tgt, idx, src, axis=0):
    return tgt.clone().index_add_(axis, idx, src)

def _segment_sum(src, seg, n):
    out = torch.zeros((n,) + src.shape[1:], dtype=src.dtype)
    return out.index_add_(0, seg, src)

def _pad(x, pw):
    flat = tuple((v for pair in reversed(pw) for v in pair))
    return torch.nn.functional.pad(x, flat)
kernel_name = 'recurrent_scan__memory_aug_recurrent_mem_tr__mixer_channel_mlp__prompt'

def setup_inputs():

    _w = lambda a: (lambda t: t.to(torch.bfloat16) if t.is_floating_point() else t)(torch.as_tensor(a))

    def _A_setup():
        B, S, Dm = (1, 2048, 640)
        H, Dh = (32, 192)
        M, seg = (8, 32)
        seg = min(seg, S)
        S = S // seg * seg
        return {'x': _w((lambda *s: torch.randn(*s, dtype=torch.bfloat16) * 0.05)(B, S, Dm)), 'mem0': _w((lambda *s: torch.randn(*s, dtype=torch.bfloat16) * 0.8)(B, M, Dm)), 'Wq': _w((lambda *s: torch.randn(*s, dtype=torch.bfloat16) * 0.8)(Dm, H, Dh) * Dm ** (-0.5)), 'Wk': _w((lambda *s: torch.randn(*s, dtype=torch.bfloat16) * 0.8)(Dm, H, Dh) * Dm ** (-0.5)), 'Wv': _w((lambda *s: torch.randn(*s, dtype=torch.bfloat16) * 0.8)(Dm, H, Dh) * Dm ** (-0.5)), 'Wo': _w((lambda *s: torch.randn(*s, dtype=torch.bfloat16) * 0.8)(H, Dh, Dm) * (H * Dh) ** (-0.5)), 'seg_len': seg}
    _A_in = _A_setup()

    def _B_setup():
        B, S, D, F = (1, 2048, 640, 1536)
        return {'x': _w((lambda *s: torch.randn(*s, dtype=torch.bfloat16) * 0.05)(B, S, D)), 'w1': _w((lambda *s: torch.randn(*s, dtype=torch.bfloat16) * 1.6)(D, F) * D ** (-0.5)), 'b1': _w((lambda *s: torch.randn(*s, dtype=torch.bfloat16) * 0.4)(F)), 'w2': _w((lambda *s: torch.randn(*s, dtype=torch.bfloat16) * 0.2)(F, D) * F ** (-0.5)), 'b2': _w((lambda *s: torch.randn(*s, dtype=torch.bfloat16) * 0.2)(D))}
    _B_in = _B_setup()
    return {'A_x': _A_in['x'], 'A_mem0': _A_in['mem0'], 'A_Wq': _A_in['Wq'], 'A_Wk': _A_in['Wk'], 'A_Wv': _A_in['Wv'], 'A_Wo': _A_in['Wo'], 'A_seg_len': _A_in['seg_len'], 'B_x': _B_in['x'], 'B_w1': _B_in['w1'], 'B_b1': _B_in['b1'], 'B_w2': _B_in['w2'], 'B_b2': _B_in['b2']}

def reference(A_x, A_mem0, A_Wq, A_Wk, A_Wv, A_Wo, A_seg_len, B_x, B_w1, B_b1, B_w2, B_b2):

    def _A_ref(x, mem0, Wq, Wk, Wv, Wo, seg_len):
        B, S, Dm = x.shape
        H, Dh = (Wq.shape[1], Wq.shape[2])
        M = mem0.shape[1]
        scale = Dh ** (-0.5)
        n_seg = S // seg_len
        L = M + seg_len
        idx = torch.arange(L)
        mask = (idx[:, None] < M) | (idx[:, None] >= idx[None, :])
        mem = mem0
        outs = []
        for s in range(n_seg):
            xs = x[:, s * seg_len:(s + 1) * seg_len, :].clone()
            h = torch.concatenate([mem, xs], axis=1)
            q = torch.einsum('btd,dhe->bhte', h, Wq)
            k = torch.einsum('btd,dhe->bhte', h, Wk)
            v = torch.einsum('btd,dhe->bhte', h, Wv)
            scores = torch.einsum('bhqe,bhke->bhqk', q, k) * scale
            scores = torch.where(mask[None, None], scores, -1000000000.0)
            p = _softmax(scores, axis=-1)
            o = torch.einsum('bhqk,bhke->bhqe', p, v)
            o = torch.einsum('bhte,hed->btd', o, Wo)
            mem = o[:, :M, :].clone()
            outs.append(o[:, M:, :])
        return torch.concatenate(outs, axis=1)

    def _B_ref(x, w1, b1, w2, b2):
        y = _layernorm(x, axis=-1)
        h = _gelu(torch.einsum('bsd,df->bsf', y, w1) + b1)
        return torch.einsum('bsf,fd->bsd', h, w2) + b2
    x = A_x
    xn = _layernorm(x, axis=-1)
    s = _A_ref(xn, A_mem0, A_Wq, A_Wk, A_Wv, A_Wo, A_seg_len)
    g = _silu(_B_ref(xn, B_w1, B_b1, B_w2, B_b2))
    return x + s * g
```

```cpp
#include <cuda_runtime.h>
#include <cuda_bf16.h>
#include <stdint.h>

typedef __nv_bfloat16 bf16;

constexpr int S_ = 2048, D_ = 640, H_ = 32, DH_ = 192, NSEG = 64, F_ = 1536;
constexpr int SPIN_LIMIT = 1 << 20;

__device__ bf16 g_xn[S_ * D_];
__device__ bf16 g_y[S_ * D_];
__device__ bf16 g_hmid[S_ * F_];
__device__ bf16 g_gate[S_ * D_];
__device__ bf16 g_qkv[3][S_ * 6144];
__device__ bf16 g_Bplain[32 * S_ * 640];
__device__ uint32_t g_B[64 * 40 * 32 * 2 * 128];
__device__ uint32_t g_mem[2][8 * 640];
__device__ uint32_t g_p[2][5][32][160];
__device__ uint32_t g_z[2][40][32][128];
__device__ int g_err;

__device__ __forceinline__ uint32_t smem_u32(const void* p) { return (uint32_t)__cvta_generic_to_shared(p); }
__device__ __forceinline__ void ldsm_x4(uint32_t& r0, uint32_t& r1, uint32_t& r2, uint32_t& r3, uint32_t addr) {
  asm volatile("ldmatrix.sync.aligned.m8n8.x4.shared.b16 {%0,%1,%2,%3}, [%4];" : "=r"(r0), "=r"(r1), "=r"(r2), "=r"(r3) : "r"(addr) : "memory");
}
__device__ __forceinline__ void ldsm_x4_t(uint32_t& r0, uint32_t& r1, uint32_t& r2, uint32_t& r3, uint32_t addr) {
  asm volatile("ldmatrix.sync.aligned.m8n8.x4.trans.shared.b16 {%0,%1,%2,%3}, [%4];" : "=r"(r0), "=r"(r1), "=r"(r2), "=r"(r3) : "r"(addr) : "memory");
}
__device__ __forceinline__ void mma_bf16(float* c, uint32_t a0, uint32_t a1, uint32_t a2, uint32_t a3, uint32_t b0, uint32_t b1) {
  asm volatile("mma.sync.aligned.m16n8k16.row.col.f32.bf16.bf16.f32 {%0,%1,%2,%3}, {%4,%5,%6,%7}, {%8,%9}, {%0,%1,%2,%3};"
               : "+f"(c[0]), "+f"(c[1]), "+f"(c[2]), "+f"(c[3]) : "r"(a0), "r"(a1), "r"(a2), "r"(a3), "r"(b0), "r"(b1));
}
__device__ __forceinline__ void mma_tf32(float* c, uint32_t a0, uint32_t a1, uint32_t a2, uint32_t a3, uint32_t b0, uint32_t b1) {
  asm volatile("mma.sync.aligned.m16n8k8.row.col.f32.tf32.tf32.f32 {%0,%1,%2,%3}, {%4,%5,%6,%7}, {%8,%9}, {%0,%1,%2,%3};"
               : "+f"(c[0]), "+f"(c[1]), "+f"(c[2]), "+f"(c[3]) : "r"(a0), "r"(a1), "r"(a2), "r"(a3), "r"(b0), "r"(b1));
}
__device__ __forceinline__ void cp_async16(uint32_t dst, const void* src) {
  asm volatile("cp.async.cg.shared.global [%0], [%1], 16;" :: "r"(dst), "l"(src) : "memory");
}
__device__ __forceinline__ void cp_async_commit() { asm volatile("cp.async.commit_group;" ::: "memory"); }
__device__ __forceinline__ void cp_async_wait0() { asm volatile("cp.async.wait_group 0;" ::: "memory"); }
__device__ __forceinline__ void bar_sync(int id, int n) { asm volatile("bar.sync %0, %1;" :: "r"(id), "r"(n) : "memory"); }
__device__ __forceinline__ void bar_arrive(int id, int n) { asm volatile("bar.arrive %0, %1;" :: "r"(id), "r"(n) : "memory"); }
__device__ __forceinline__ uint4 ld_rlx4(const uint32_t* p) {
  uint4 v;
  asm volatile("ld.relaxed.gpu.global.v4.u32 {%0,%1,%2,%3}, [%4];" : "=r"(v.x), "=r"(v.y), "=r"(v.z), "=r"(v.w) : "l"(p) : "memory");
  return v;
}
__device__ __forceinline__ uint32_t ld_rlx1(const uint32_t* p) {
  uint32_t v;
  asm volatile("ld.relaxed.gpu.global.u32 %0, [%1];" : "=r"(v) : "l"(p) : "memory");
  return v;
}
__device__ __forceinline__ void st_rlx4(uint32_t* p, uint32_t a, uint32_t b, uint32_t c, uint32_t d) {
  asm volatile("st.relaxed.gpu.global.v4.u32 [%0], {%1,%2,%3,%4};" :: "l"(p), "r"(a), "r"(b), "r"(c), "r"(d) : "memory");
}
__device__ __forceinline__ void st_rlx1(uint32_t* p, uint32_t a) {
  asm volatile("st.relaxed.gpu.global.u32 [%0], %1;" :: "l"(p), "r"(a) : "memory");
}
__device__ __forceinline__ void mbar_init(uint32_t bar, int count) {
  asm volatile("mbarrier.init.shared::cta.b64 [%0], %1;" :: "r"(bar), "r"(count) : "memory");
}
__device__ __forceinline__ void mbar_arrive(uint32_t bar) {
  asm volatile("mbarrier.arrive.shared::cta.b64 _, [%0];" :: "r"(bar) : "memory");
}
__device__ __forceinline__ void mbar_arrive_tx(uint32_t bar, uint32_t tx) {
  asm volatile("mbarrier.arrive.expect_tx.shared::cta.b64 _, [%0], %1;" :: "r"(bar), "r"(tx) : "memory");
}
__device__ __forceinline__ void mbar_wait(uint32_t bar, uint32_t parity) {
  uint32_t done = 0;
  int guard = 0;
  while (true) {
    asm volatile("{\n.reg .pred p;\nmbarrier.try_wait.parity.acquire.cluster.shared::cta.b64 p, [%1], %2;\nselp.u32 %0, 1, 0, p;\n}"
                 : "=r"(done) : "r"(bar), "r"(parity) : "memory");
    if (done) break;
    if (++guard > SPIN_LIMIT) { g_err = 1; break; }
  }
}
__device__ __forceinline__ uint32_t mapa(uint32_t addr, uint32_t rank) {
  uint32_t r;
  asm volatile("mapa.shared::cluster.u32 %0, %1, %2;" : "=r"(r) : "r"(addr), "r"(rank));
  return r;
}
__device__ __forceinline__ void st_async1(uint32_t addr, uint32_t v, uint32_t bar) {
  asm volatile("st.async.weak.shared::cluster.mbarrier::complete_tx::bytes.b32 [%0], %1, [%2];" :: "r"(addr), "r"(v), "r"(bar) : "memory");
}
__device__ __forceinline__ void st_async2(uint32_t addr, float a, float b, uint32_t bar) {
  asm volatile("st.async.weak.shared::cluster.mbarrier::complete_tx::bytes.v2.f32 [%0], {%1,%2}, [%3];" :: "r"(addr), "f"(a), "f"(b), "r"(bar) : "memory");
}
__device__ __forceinline__ void st_async4(uint32_t addr, float a, float b, float c, float d, uint32_t bar) {
  asm volatile("st.async.weak.shared::cluster.mbarrier::complete_tx::bytes.v4.f32 [%0], {%1,%2,%3,%4}, [%5];" :: "r"(addr), "f"(a), "f"(b), "f"(c), "f"(d), "r"(bar) : "memory");
}
__device__ __forceinline__ void cluster_sync() {
  asm volatile("barrier.cluster.arrive.release.aligned;\nbarrier.cluster.wait.acquire.aligned;" ::: "memory");
}
__device__ __forceinline__ float bf16r(float x) { return __bfloat162float(__float2bfloat16_rn(x)); }
__device__ __forceinline__ uint32_t pack_bf16(float lo, float hi) {
  uint32_t r;
  asm("cvt.rn.bf16x2.f32 %0, %1, %2;" : "=r"(r) : "f"(hi), "f"(lo));
  return r;
}
__device__ __forceinline__ uint32_t to_tf32(float x) {
  uint32_t r;
  asm("cvt.rna.tf32.f32 %0, %1;" : "=r"(r) : "f"(x));
  return r;
}

__device__ __forceinline__ void ln_row(const float (&v)[20], float (&o)[20]) {
  float s = 0.f;
#pragma unroll
  for (int i = 0; i < 20; i++) s += v[i];
#pragma unroll
  for (int m = 16; m; m >>= 1) s += __shfl_xor_sync(0xffffffffu, s, m);
  float mean = s * (1.f / 640.f);
  float q = 0.f;
#pragma unroll
  for (int i = 0; i < 20; i++) { float d = v[i] - mean; q += d * d; }
#pragma unroll
  for (int m = 16; m; m >>= 1) q += __shfl_xor_sync(0xffffffffu, q, m);
  float var = bf16r(q * (1.f / 640.f));
  float mb = bf16r(mean);
  float den = bf16r(sqrtf(bf16r(var + 1e-5f)));
#pragma unroll
  for (int i = 0; i < 20; i++) o[i] = bf16r(bf16r(v[i] - mb) / den);
}

__global__ void __launch_bounds__(256) ln_kernel(const bf16* __restrict__ x, const bf16* __restrict__ mem0) {
  int warp = (blockIdx.x * 256 + threadIdx.x) >> 5, lane = threadIdx.x & 31;
  if (blockIdx.x == 0) {
    for (int i = threadIdx.x; i < 8 * 640; i += 256) {
      uint32_t b = __bfloat16_as_ushort(mem0[i]);
      g_mem[0][i] = (b << 16) | 1u;
    }
  }
  if (warp >= S_) return;
  const uint32_t* xr = reinterpret_cast<const uint32_t*>(x + (size_t)warp * D_);
  float v[20], o[20], o2[20];
#pragma unroll
  for (int i = 0; i < 10; i++) {
    uint32_t w = xr[i * 32 + lane];
    v[2 * i] = __uint_as_float(w << 16);
    v[2 * i + 1] = __uint_as_float(w & 0xffff0000u);
  }
  ln_row(v, o);
  ln_row(o, o2);
  uint32_t* xo = reinterpret_cast<uint32_t*>(g_xn + (size_t)warp * D_);
  uint32_t* yo = reinterpret_cast<uint32_t*>(g_y + (size_t)warp * D_);
#pragma unroll
  for (int i = 0; i < 10; i++) {
    xo[i * 32 + lane] = pack_bf16(o[2 * i], o[2 * i + 1]);
    yo[i * 32 + lane] = pack_bf16(o2[2 * i], o2[2 * i + 1]);
  }
}

template <int EPI>
__global__ void __launch_bounds__(256) gemm_kernel(const bf16* __restrict__ A, int lda, long long sA,
                                                   const bf16* __restrict__ B, int ldb, long long sB,
                                                   bf16* __restrict__ C, int ldc, long long sC,
                                                   const bf16* __restrict__ bias, int K) {
  constexpr int BM = 128, BN = 128, BK = 32;
  __shared__ __align__(16) bf16 As[2][BM][BK + 8];
  __shared__ __align__(16) bf16 Bs[2][BK][BN + 8];
  A += sA * blockIdx.z; B += sB * blockIdx.z; C += sC * blockIdx.z;
  int tid = threadIdx.x, warp = tid >> 5, lane = tid & 31;
  int m0 = blockIdx.y * BM, n0 = blockIdx.x * BN;
  int wm = (warp >> 2) * 64, wn = (warp & 3) * 32;
  float acc[4][4][4];
#pragma unroll
  for (int i = 0; i < 4; i++)
#pragma unroll
    for (int j = 0; j < 4; j++)
#pragma unroll
      for (int k = 0; k < 4; k++) acc[i][j][k] = 0.f;
  auto load = [&](int buf, int k0) {
#pragma unroll
    for (int i = 0; i < 2; i++) {
      int idx = tid + i * 256;
      int r = idx >> 2, c = (idx & 3) * 8;
      cp_async16(smem_u32(&As[buf][r][c]), A + (size_t)(m0 + r) * lda + k0 + c);
      int r2 = idx >> 4, c2 = (idx & 15) * 8;
      cp_async16(smem_u32(&Bs[buf][r2][c2]), B + (size_t)(k0 + r2) * ldb + n0 + c2);
    }
    cp_async_commit();
  };
  load(0, 0);
  int nk = K / BK;
  for (int kt = 0; kt < nk; kt++) {
    cp_async_wait0();
    __syncthreads();
    if (kt + 1 < nk) load((kt + 1) & 1, (kt + 1) * BK);
    int buf = kt & 1;
#pragma unroll
    for (int ks = 0; ks < 2; ks++) {
      uint32_t a[4][4], b[2][4];
#pragma unroll
      for (int i = 0; i < 4; i++)
        ldsm_x4(a[i][0], a[i][1], a[i][2], a[i][3], smem_u32(&As[buf][wm + i * 16 + (lane & 15)][ks * 16 + (lane >> 4) * 8]));
#pragma unroll
      for (int j = 0; j < 2; j++)
        ldsm_x4_t(b[j][0], b[j][1], b[j][2], b[j][3], smem_u32(&Bs[buf][ks * 16 + (lane & 15)][wn + j * 16 + (lane >> 4) * 8]));
#pragma unroll
      for (int i = 0; i < 4; i++)
#pragma unroll
        for (int j = 0; j < 4; j++)
          mma_bf16(acc[i][j], a[i][0], a[i][1], a[i][2], a[i][3], b[j >> 1][(j & 1) * 2], b[j >> 1][(j & 1) * 2 + 1]);
    }
  }
  int g = lane >> 2, q = lane & 3;
#pragma unroll
  for (int i = 0; i < 4; i++)
#pragma unroll
    for (int j = 0; j < 4; j++)
#pragma unroll
      for (int hh = 0; hh < 2; hh++) {
        int r = m0 + wm + i * 16 + g + hh * 8, c = n0 + wn + j * 8 + q * 2;
        float v0 = acc[i][j][hh * 2], v1 = acc[i][j][hh * 2 + 1];
        if (EPI != 0) {
          v0 = bf16r(bf16r(v0) + __bfloat162float(bias[c]));
          v1 = bf16r(bf16r(v1) + __bfloat162float(bias[c + 1]));
          if (EPI == 1) {
            v0 = 0.5f * v0 * (1.f + tanhf(0.7978845608028654f * (v0 + 0.044715f * v0 * v0 * v0)));
            v1 = 0.5f * v1 * (1.f + tanhf(0.7978845608028654f * (v1 + 0.044715f * v1 * v1 * v1)));
          } else {
            v0 = v0 / (1.f + __expf(-v0));
            v1 = v1 / (1.f + __expf(-v1));
          }
        }
        *reinterpret_cast<uint32_t*>(C + (size_t)r * ldc + c) = pack_bf16(v0, v1);
      }
}

__global__ void repackB_kernel() {
  size_t idx = (size_t)blockIdx.x * 256 + threadIdx.x;
  if (idx >= (size_t)64 * 40 * 32 * 2 * 128) return;
  int r = idx & 3, lane = (idx >> 2) & 31, ks = (idx >> 7) & 1, h = (idx >> 8) & 31;
  size_t rest = idx >> 13;
  int slab = rest % 40, seg = rest / 40;
  int g = lane >> 2, i = lane & 3;
  int col = slab * 16 + g + (r & 1) * 8;
  int key = seg * 32 + ks * 16 + 2 * i + (r >> 1) * 8;
  const bf16* src = g_Bplain + ((size_t)h * S_ + key) * 640 + col;
  uint32_t lo = __bfloat16_as_ushort(src[0]), hi = __bfloat16_as_ushort(src[640]);
  g_B[idx] = lo | (hi << 16);
}

struct QKSmem {
  bf16 w2[192][200];
  bf16 stage[112][200];
  bf16 mem[8][648];
  float part[3][3][128][4];
  bf16 qm[8][104];
  bf16 km[8][104];
  bf16 qx[2][32][104];
  bf16 kx[2][32][104];
  float scm[2][5][32][2];
  float scx[2][2][5][32][4];
  unsigned long long bar[4];
};
struct VOSmem {
  bf16 wv2[256][104];
  bf16 wo2[192][72];
  uint32_t Bst[2][32][2][128];
  bf16 mem[8][648];
  float pT0[3][128][4];
  float pT1[3][128][4];
  bf16 vm[8][200];
  float red[4][5][128];
  unsigned long long bar[4];
};
constexpr int CHAIN_SMEM = (sizeof(QKSmem) > sizeof(VOSmem) ? sizeof(QKSmem) : sizeof(VOSmem)) + 128;

template <int NQ>
__device__ __forceinline__ void poll_mem(const uint32_t* gm, uint32_t tag, int c0, bf16* sm, int tid) {
  constexpr int TOT = 8 * NQ, NI = (TOT + 127) / 128;
  uint4 v[NI];
#pragma unroll
  for (int i = 0; i < NI; i++) {
    int idx = tid + 128 * i;
    if (idx < TOT) v[i] = ld_rlx4(gm + (idx / NQ) * 640 + c0 + 4 * (idx % NQ));
  }
#pragma unroll
  for (int i = 0; i < NI; i++) {
    int idx = tid + 128 * i;
    if (idx < TOT) {
      int guard = 0;
      while ((((v[i].x ^ tag) | (v[i].y ^ tag) | (v[i].z ^ tag) | (v[i].w ^ tag)) & 0xffffu) != 0) {
        v[i] = ld_rlx4(gm + (idx / NQ) * 640 + c0 + 4 * (idx % NQ));
        if (++guard > SPIN_LIMIT) { g_err = 2; break; }
      }
      uint2 o;
      o.x = (v[i].x >> 16) | (v[i].y & 0xffff0000u);
      o.y = (v[i].z >> 16) | (v[i].w & 0xffff0000u);
      *reinterpret_cast<uint2*>(sm + (idx / NQ) * 648 + c0 + 4 * (idx % NQ)) = o;
    }
  }
}

__device__ __forceinline__ float4 lds4(const float* p) { return *reinterpret_cast<const float4*>(p); }
__device__ __forceinline__ void sts4(float* p, const float* v) { *reinterpret_cast<float4*>(p) = make_float4(v[0], v[1], v[2], v[3]); }

__device__ __forceinline__ void softmax_row(float (&s)[5][2], uint32_t (&w)[5]) {
  float m = -3.0e38f;
#pragma unroll
  for (int j = 0; j < 5; j++) m = fmaxf(m, fmaxf(s[j][0], s[j][1]));
  m = fmaxf(m, __shfl_xor_sync(0xffffffffu, m, 1));
  m = fmaxf(m, __shfl_xor_sync(0xffffffffu, m, 2));
  float sum = 0.f;
#pragma unroll
  for (int j = 0; j < 5; j++) {
    s[j][0] = __expf(s[j][0] - m); s[j][1] = __expf(s[j][1] - m);
    sum += s[j][0] + s[j][1];
  }
  sum += __shfl_xor_sync(0xffffffffu, sum, 1);
  sum += __shfl_xor_sync(0xffffffffu, sum, 2);
  float inv = 1.f / sum;
#pragma unroll
  for (int j = 0; j < 5; j++) w[j] = pack_bf16(s[j][0] * inv, s[j][1] * inv);
}

struct ChainParams {
  const bf16 *Wq, *Wk, *Wv, *Wo, *x;
  bf16* out;
};

constexpr float SCALE = 0.07216878364870322f;

__global__ void __cluster_dims__(2, 1, 1) __launch_bounds__(384, 1) chain_kernel(ChainParams P) {
  extern __shared__ __align__(128) uint8_t smem_raw[];
  const int tid = threadIdx.x, wg = tid >> 7, wt = tid & 127, warp = wt >> 5, lane = tid & 31;
  const int g = lane >> 2, qi = lane & 3;
  const int b = blockIdx.x, rank = b & 1, pair = b >> 1, h = pair >> 1, type = pair & 1;

  if (type == 0) {
    QKSmem& sm = *reinterpret_cast<QKSmem*>(smem_raw);
    const uint32_t barM = smem_u32(&sm.bar[0]), barX = smem_u32(&sm.bar[1]);
    if (tid == 0) { mbar_init(barM, 4); mbar_init(barX, 4); asm volatile("fence.mbarrier_init.release.cluster;" ::: "memory"); }
    const bf16* wq = P.Wq + h * DH_ + 96 * rank;
    const bf16* wk = P.Wk + h * DH_ + 96 * rank;
    for (int idx = tid; idx < 192 * 24; idx += 384) {
      int r = idx / 24, c = idx % 24;
      const bf16* src = (c < 12 ? wq + c * 8 : wk + (c - 12) * 8) + (size_t)(448 + r) * 6144;
      cp_async16(smem_u32(&sm.w2[r][c * 8]), src);
    }
    cp_async_commit();
    auto stage_issue = [&](int r0) {
      for (int idx = tid; idx < 112 * 24; idx += 384) {
        int r = idx / 24, c = idx % 24;
        const bf16* src = (c < 12 ? wq + c * 8 : wk + (c - 12) * 8) + (size_t)(r0 + r) * 6144;
        cp_async16(smem_u32(&sm.stage[r][c * 8]), src);
      }
      cp_async_commit();
      cp_async_wait0();
    };
    cluster_sync();
    if (wg < 2) {
      asm volatile("setmaxnreg.inc.sync.aligned.u32 200;");
      uint32_t W[3][14][4];
#pragma unroll
      for (int r = 0; r < 4; r++) {
        stage_issue(112 * r);
        __syncthreads();
        if ((r >> 1) == wg) {
#pragma unroll
          for (int T = 0; T < 3; T++)
#pragma unroll
            for (int ks = 0; ks < 7; ks++) {
              uint32_t addr = smem_u32(&sm.stage[ks * 16 + (lane & 7) + ((lane >> 4) & 1) * 8][T * 64 + warp * 16 + ((lane >> 3) & 1) * 8]);
              ldsm_x4_t(W[T][(r & 1) * 7 + ks][0], W[T][(r & 1) * 7 + ks][1], W[T][(r & 1) * 7 + ks][2], W[T][(r & 1) * 7 + ks][3], addr);
            }
        }
        __syncthreads();
      }
      const uint32_t baddr = smem_u32(&sm.mem[lane & 7][224 * wg + (lane >> 3) * 8]);
      for (int t = 0; t < NSEG; t++) {
        poll_mem<56>(g_mem[t & 1], t + 1, 224 * wg, &sm.mem[0][0], wt);
        bar_sync(1 + wg, 128);
        float acc[3][4];
#pragma unroll
        for (int T = 0; T < 3; T++) { acc[T][0] = acc[T][1] = acc[T][2] = acc[T][3] = 0.f; }
#pragma unroll
        for (int kp = 0; kp < 7; kp++) {
          uint32_t b0, b1, b2, b3;
          ldsm_x4(b0, b1, b2, b3, baddr + kp * 64);
#pragma unroll
          for (int T = 0; T < 3; T++) mma_bf16(acc[T], W[T][2 * kp][0], W[T][2 * kp][1], W[T][2 * kp][2], W[T][2 * kp][3], b0, b1);
#pragma unroll
          for (int T = 0; T < 3; T++) mma_bf16(acc[T], W[T][2 * kp + 1][0], W[T][2 * kp + 1][1], W[T][2 * kp + 1][2], W[T][2 * kp + 1][3], b2, b3);
        }
#pragma unroll
        for (int T = 0; T < 3; T++) sts4(&sm.part[wg][T][wt][0], acc[T]);
        bar_sync(4, 384);
        {
          float4 a0 = lds4(&sm.part[0][wg][wt][0]), a1 = lds4(&sm.part[1][wg][wt][0]), a2 = lds4(&sm.part[2][wg][wt][0]);
          float r0 = a0.x + a1.x + a2.x, r1 = a0.y + a1.y + a2.y, r2 = a0.z + a1.z + a2.z, r3 = a0.w + a1.w + a2.w;
          int mm = wg * 64 + warp * 16 + g;
          bf16* d0 = (mm < 96) ? &sm.qm[0][mm] : &sm.km[0][mm - 96];
          d0[(2 * qi) * 104] = __float2bfloat16_rn(r0);
          d0[(2 * qi + 1) * 104] = __float2bfloat16_rn(r1);
          d0[(2 * qi) * 104 + 8] = __float2bfloat16_rn(r2);
          d0[(2 * qi + 1) * 104 + 8] = __float2bfloat16_rn(r3);
        }
        bar_arrive(5, 384);
      }
    } else {
      asm volatile("setmaxnreg.dec.sync.aligned.u32 104;");
#pragma unroll
      for (int r = 0; r < 4; r++) {
        stage_issue(112 * r);
        __syncthreads();
        __syncthreads();
      }
      auto load_qkx = [&](int t) {
        const bf16* q = g_qkv[0] + (size_t)(t * 32) * 6144 + h * DH_ + 96 * rank;
        const bf16* k = g_qkv[1] + (size_t)(t * 32) * 6144 + h * DH_ + 96 * rank;
#pragma unroll
        for (int i = 0; i < 3; i++) {
          int idx = wt + 128 * i;
          int r = idx / 12, c = idx % 12;
          cp_async16(smem_u32(&sm.qx[t & 1][r][c * 8]), q + (size_t)r * 6144 + c * 8);
          cp_async16(smem_u32(&sm.kx[t & 1][r][c * 8]), k + (size_t)r * 6144 + c * 8);
        }
        cp_async_commit();
      };
      load_qkx(0);
      const uint32_t baddr = smem_u32(&sm.mem[lane & 7][448 + (lane >> 3) * 8]);
      const uint32_t waddr = smem_u32(&sm.w2[(lane & 7) + ((lane >> 4) & 1) * 8][warp * 16 + ((lane >> 3) & 1) * 8]);
      const uint32_t barM0 = mapa(barM, 0), barX1 = mapa(barX, 1);
      const uint32_t scm_r = mapa(smem_u32(&sm.scm[1][0][lane][0]), 0);
      const uint32_t scx_r = mapa(smem_u32(&sm.scx[0][0][0][lane][0]), 1);
      for (int t = 0; t < NSEG; t++) {
        poll_mem<48>(g_mem[t & 1], t + 1, 448, &sm.mem[0][0], wt);
        bar_sync(3, 128);
        float acc[3][4];
#pragma unroll
        for (int T = 0; T < 3; T++) { acc[T][0] = acc[T][1] = acc[T][2] = acc[T][3] = 0.f; }
#pragma unroll
        for (int kp = 0; kp < 6; kp++) {
          uint32_t b0, b1, b2, b3;
          ldsm_x4(b0, b1, b2, b3, baddr + kp * 64);
#pragma unroll
          for (int T = 0; T < 3; T++) {
            uint32_t a0, a1, a2, a3;
            ldsm_x4_t(a0, a1, a2, a3, waddr + (2 * kp) * 16 * 400 + T * 128);
            mma_bf16(acc[T], a0, a1, a2, a3, b0, b1);
          }
#pragma unroll
          for (int T = 0; T < 3; T++) {
            uint32_t a0, a1, a2, a3;
            ldsm_x4_t(a0, a1, a2, a3, waddr + (2 * kp + 1) * 16 * 400 + T * 128);
            mma_bf16(acc[T], a0, a1, a2, a3, b2, b3);
          }
        }
#pragma unroll
        for (int T = 0; T < 3; T++) sts4(&sm.part[2][T][wt][0], acc[T]);
        bar_sync(4, 384);
        {
          float4 a0 = lds4(&sm.part[0][2][wt][0]), a1 = lds4(&sm.part[1][2][wt][0]), a2 = lds4(&sm.part[2][2][wt][0]);
          float r0 = a0.x + a1.x + a2.x, r1 = a0.y + a1.y + a2.y, r2 = a0.z + a1.z + a2.z, r3 = a0.w + a1.w + a2.w;
          bf16* d0 = &sm.km[0][32 + warp * 16 + g];
          d0[(2 * qi) * 104] = __float2bfloat16_rn(r0);
          d0[(2 * qi + 1) * 104] = __float2bfloat16_rn(r1);
          d0[(2 * qi) * 104 + 8] = __float2bfloat16_rn(r2);
          d0[(2 * qi + 1) * 104 + 8] = __float2bfloat16_rn(r3);
        }
        cp_async_wait0();
        bar_sync(5, 384);
        const int xb = t & 1;
        {
          float sc[4] = {0.f, 0.f, 0.f, 0.f}, s0[4] = {0.f, 0.f, 0.f, 0.f};
          const uint32_t qa = smem_u32(&sm.qm[lane & 7][(lane >> 3) * 8]);
          const uint32_t ka = smem_u32(&sm.kx[xb][warp * 8 + (lane & 7)][(lane >> 3) * 8]);
          const uint32_t kma = smem_u32(&sm.km[lane & 7][(lane >> 3) * 8]);
#pragma unroll
          for (int kp = 0; kp < 3; kp++) {
            uint32_t a0, a1, a2, a3, b0, b1, b2, b3;
            ldsm_x4(a0, a1, a2, a3, qa + kp * 64);
            ldsm_x4(b0, b1, b2, b3, ka + kp * 64);
            mma_bf16(sc, a0, 0u, a1, 0u, b0, b1);
            mma_bf16(sc, a2, 0u, a3, 0u, b2, b3);
            if (warp == 0) {
              ldsm_x4(b0, b1, b2, b3, kma + kp * 64);
              mma_bf16(s0, a0, 0u, a1, 0u, b0, b1);
              mma_bf16(s0, a2, 0u, a3, 0u, b2, b3);
            }
          }
          if (rank == 0) {
            *reinterpret_cast<float2*>(&sm.scm[0][warp + 1][lane][0]) = make_float2(sc[0], sc[1]);
            if (warp == 0) *reinterpret_cast<float2*>(&sm.scm[0][0][lane][0]) = make_float2(s0[0], s0[1]);
            __syncwarp();
            if (lane == 0) { if (warp == 0) mbar_arrive_tx(barM, 1280); else mbar_arrive(barM); }
          } else {
            st_async2(scm_r + (warp + 1) * 256, sc[0], sc[1], barM0);
            if (warp == 0) st_async2(scm_r, s0[0], s0[1], barM0);
          }
        }
        const uint32_t phase = ((((t >> 1) & 1) ^ 1) != 0) ? 0x80008000u : 0u;
        if (rank == 0 && warp == 0) {
          mbar_wait(barM, t & 1);
          float s[5][2];
#pragma unroll
          for (int j = 0; j < 5; j++) {
            float2 u = *reinterpret_cast<float2*>(&sm.scm[0][j][lane][0]);
            float2 v = *reinterpret_cast<float2*>(&sm.scm[1][j][lane][0]);
            s[j][0] = bf16r(bf16r(u.x + v.x) * SCALE);
            s[j][1] = bf16r(bf16r(u.y + v.y) * SCALE);
          }
          uint32_t w[5];
          softmax_row(s, w);
          uint32_t* dst = &g_p[t & 1][0][h][0];
          st_rlx4(dst + lane * 4, w[1] | phase, w[2] | phase, w[3] | phase, w[4] | phase);
          st_rlx1(dst + 128 + lane, w[0] | phase);
        }
        {
          const int mt = warp & 1;
          const int nt0 = (warp >> 1) ? 3 : 0, nn = (warp >> 1) ? 2 : 3;
          float sc[3][4];
#pragma unroll
          for (int j = 0; j < 3; j++) { sc[j][0] = sc[j][1] = sc[j][2] = sc[j][3] = 0.f; }
          const uint32_t qa = smem_u32(&sm.qx[xb][mt * 16 + (lane & 15)][(lane >> 4) * 8]);
#pragma unroll
          for (int kp = 0; kp < 3; kp++) {
            uint32_t a[2][4];
            ldsm_x4(a[0][0], a[0][1], a[0][2], a[0][3], qa + kp * 64);
            ldsm_x4(a[1][0], a[1][1], a[1][2], a[1][3], qa + kp * 64 + 32);
#pragma unroll
            for (int j = 0; j < 3; j++) {
              if (j < nn) {
                int nt = nt0 + j;
                uint32_t ka = (nt == 0) ? smem_u32(&sm.km[lane & 7][(lane >> 3) * 8]) : smem_u32(&sm.kx[xb][(nt - 1) * 8 + (lane & 7)][(lane >> 3) * 8]);
                uint32_t b0, b1, b2, b3;
                ldsm_x4(b0, b1, b2, b3, ka + kp * 64);
                mma_bf16(sc[j], a[0][0], a[0][1], a[0][2], a[0][3], b0, b1);
                mma_bf16(sc[j], a[1][0], a[1][1], a[1][2], a[1][3], b2, b3);
              }
            }
          }
          if (rank == 1) {
#pragma unroll
            for (int j = 0; j < 3; j++) if (j < nn) sts4(&sm.scx[1][mt][nt0 + j][lane][0], sc[j]);
            __syncwarp();
            if (lane == 0) { if (warp == 0) mbar_arrive_tx(barX, 5120); else mbar_arrive(barX); }
          } else {
#pragma unroll
            for (int j = 0; j < 3; j++) if (j < nn) st_async4(scx_r + (mt * 5 + nt0 + j) * 512, sc[j][0], sc[j][1], sc[j][2], sc[j][3], barX1);
          }
        }
        if (rank == 1 && warp < 2) {
          mbar_wait(barX, t & 1);
          float sa[5][2], sb[5][2];
          const int qa_ = warp * 16 + g, qb_ = qa_ + 8;
#pragma unroll
          for (int j = 0; j < 5; j++) {
            float4 u = lds4(&sm.scx[0][warp][j][lane][0]);
            float4 v = lds4(&sm.scx[1][warp][j][lane][0]);
            sa[j][0] = bf16r(bf16r(u.x + v.x) * SCALE);
            sa[j][1] = bf16r(bf16r(u.y + v.y) * SCALE);
            sb[j][0] = bf16r(bf16r(u.z + v.z) * SCALE);
            sb[j][1] = bf16r(bf16r(u.w + v.w) * SCALE);
            if (j > 0) {
              int k0 = (j - 1) * 8 + 2 * qi;
              if (k0 > qa_) sa[j][0] = -1e9f;
              if (k0 + 1 > qa_) sa[j][1] = -1e9f;
              if (k0 > qb_) sb[j][0] = -1e9f;
              if (k0 + 1 > qb_) sb[j][1] = -1e9f;
            }
          }
          uint32_t w[5];
          softmax_row(sa, w);
          uint32_t* dst = &g_p[t & 1][1 + 2 * warp][h][0];
          st_rlx4(dst + lane * 4, w[1] | phase, w[2] | phase, w[3] | phase, w[4] | phase);
          st_rlx1(dst + 128 + lane, w[0] | phase);
          softmax_row(sb, w);
          dst = &g_p[t & 1][2 + 2 * warp][h][0];
          st_rlx4(dst + lane * 4, w[1] | phase, w[2] | phase, w[3] | phase, w[4] | phase);
          st_rlx1(dst + 128 + lane, w[0] | phase);
        }
        bar_sync(6, 128);
        if (t + 1 < NSEG) load_qkx(t + 1);
      }
    }
  } else {
    VOSmem& sm = *reinterpret_cast<VOSmem*>(smem_raw);
    const uint32_t barV = smem_u32(&sm.bar[0]);
    if (tid == 0) { mbar_init(barV, 6); asm volatile("fence.mbarrier_init.release.cluster;" ::: "memory"); }
    const bf16* wv = P.Wv + h * DH_ + 96 * rank;
    const bf16* wo = P.Wo + (size_t)h * DH_ * 640 + 320 * rank;
    for (int idx = tid; idx < 256 * 12; idx += 384) {
      int r = idx / 12, c = idx % 12;
      cp_async16(smem_u32(&sm.wv2[r][c * 8]), wv + (size_t)(384 + r) * 6144 + c * 8);
    }
    for (int idx = tid; idx < 192 * 8; idx += 384) {
      int r = idx / 8, c = idx % 8;
      cp_async16(smem_u32(&sm.wo2[r][c * 8]), wo + (size_t)r * 640 + 256 + c * 8);
    }
    cp_async_commit();
    bf16* stg = reinterpret_cast<bf16*>(&sm.Bst[0][0][0][0]);
    auto stage_v = [&](int w) {
      for (int idx = tid; idx < 192 * 12; idx += 384) {
        int r = idx / 12, c = idx % 12;
        cp_async16(smem_u32(stg + r * 104 + c * 8), wv + (size_t)(192 * w + r) * 6144 + c * 8);
      }
      cp_async_commit();
      cp_async_wait0();
    };
    auto stage_o = [&](int w) {
      for (int idx = tid; idx < 192 * 16; idx += 384) {
        int r = idx / 16, c = idx % 16;
        cp_async16(smem_u32(stg + r * 136 + c * 8), wo + (size_t)r * 640 + 128 * w + c * 8);
      }
      cp_async_commit();
      cp_async_wait0();
    };
    cluster_sync();
    const uint32_t barV_r = mapa(barV, rank ^ 1);
    const uint32_t vbaddr = smem_u32(&sm.vm[lane & 7][(lane >> 3) * 8]);
    if (wg < 2) {
      asm volatile("setmaxnreg.inc.sync.aligned.u32 200;");
      uint32_t W0[12][4], W1[6][4], WO[2][12][4];
#pragma unroll
      for (int r = 0; r < 2; r++) {
        stage_v(r);
        __syncthreads();
        if (r == wg) {
#pragma unroll
          for (int ks = 0; ks < 12; ks++) {
            uint32_t addr = smem_u32(stg + (ks * 16 + (lane & 7) + ((lane >> 4) & 1) * 8) * 104 + warp * 16 + ((lane >> 3) & 1) * 8);
            ldsm_x4_t(W0[ks][0], W0[ks][1], W0[ks][2], W0[ks][3], addr);
          }
#pragma unroll
          for (int ks = 0; ks < 6; ks++) {
            uint32_t addr = smem_u32(stg + (((warp >> 1) * 6 + ks) * 16 + (lane & 7) + ((lane >> 4) & 1) * 8) * 104 + 64 + (warp & 1) * 16 + ((lane >> 3) & 1) * 8);
            ldsm_x4_t(W1[ks][0], W1[ks][1], W1[ks][2], W1[ks][3], addr);
          }
        }
        __syncthreads();
        stage_o(r);
        __syncthreads();
        if (r == wg) {
#pragma unroll
          for (int T = 0; T < 2; T++)
#pragma unroll
            for (int ks = 0; ks < 12; ks++) {
              uint32_t addr = smem_u32(stg + (ks * 16 + (lane & 7) + ((lane >> 4) & 1) * 8) * 136 + T * 64 + warp * 16 + ((lane >> 3) & 1) * 8);
              ldsm_x4_t(WO[T][ks][0], WO[T][ks][1], WO[T][ks][2], WO[T][ks][3], addr);
            }
        }
        __syncthreads();
      }
      const uint32_t baddr = smem_u32(&sm.mem[lane & 7][192 * wg + (lane >> 3) * 8]);
      for (int t = 0; t < NSEG; t++) {
        poll_mem<48>(g_mem[t & 1], t + 1, 192 * wg, &sm.mem[0][0], wt);
        bar_sync(1 + wg, 128);
        float a0[4] = {0.f, 0.f, 0.f, 0.f}, a0b[4] = {0.f, 0.f, 0.f, 0.f}, a1[4] = {0.f, 0.f, 0.f, 0.f};
#pragma unroll
        for (int kp = 0; kp < 6; kp++) {
          uint32_t b0, b1, b2, b3;
          ldsm_x4(b0, b1, b2, b3, baddr + kp * 64);
          mma_bf16(a0, W0[2 * kp][0], W0[2 * kp][1], W0[2 * kp][2], W0[2 * kp][3], b0, b1);
          mma_bf16(a0b, W0[2 * kp + 1][0], W0[2 * kp + 1][1], W0[2 * kp + 1][2], W0[2 * kp + 1][3], b2, b3);
          if ((kp < 3) == (warp < 2)) {
            const int j = 2 * (kp % 3);
            mma_bf16(a1, W1[j][0], W1[j][1], W1[j][2], W1[j][3], b0, b1);
            mma_bf16(a1, W1[j + 1][0], W1[j + 1][1], W1[j + 1][2], W1[j + 1][3], b2, b3);
          }
        }
#pragma unroll
        for (int i = 0; i < 4; i++) a0[i] += a0b[i];
        sts4(&sm.pT0[wg][wt][0], a0);
        sts4(&sm.pT1[wg][wt][0], a1);
        bar_sync(4, 384);
        if (wg == 0 || warp < 2) {
          float r[4];
          int f;
          if (wg == 0) {
            float4 x0 = lds4(&sm.pT0[0][wt][0]), x1 = lds4(&sm.pT0[1][wt][0]), x2 = lds4(&sm.pT0[2][wt][0]);
            r[0] = x0.x + x1.x + x2.x; r[1] = x0.y + x1.y + x2.y; r[2] = x0.z + x1.z + x2.z; r[3] = x0.w + x1.w + x2.w;
            f = warp * 16 + g;
          } else {
            r[0] = r[1] = r[2] = r[3] = 0.f;
#pragma unroll
            for (int w2 = 0; w2 < 3; w2++) {
              float4 x0 = lds4(&sm.pT1[w2][wt][0]), x1 = lds4(&sm.pT1[w2][wt + 64][0]);
              r[0] += x0.x + x1.x; r[1] += x0.y + x1.y; r[2] += x0.z + x1.z; r[3] += x0.w + x1.w;
            }
            f = 64 + warp * 16 + g;
          }
          const bool odd = g & 1;
          float s0 = odd ? r[0] : r[1], s1 = odd ? r[2] : r[3];
          float o0 = __shfl_xor_sync(0xffffffffu, s0, 4), o1 = __shfl_xor_sync(0xffffffffu, s1, 4);
          uint32_t wA, wB;
          if (!odd) { wA = pack_bf16(r[0], o0); wB = pack_bf16(r[2], o1); }
          else { wA = pack_bf16(o0, r[1]); wB = pack_bf16(o1, r[3]); }
          int row = 2 * qi + (odd ? 1 : 0), fe = 96 * rank + (f & ~1);
          uint32_t la = smem_u32(&sm.vm[row][fe]);
          asm volatile("st.shared.u32 [%0], %1;" :: "r"(la), "r"(wA) : "memory");
          asm volatile("st.shared.u32 [%0], %1;" :: "r"(la + 16), "r"(wB) : "memory");
          uint32_t ra = mapa(la, rank ^ 1);
          st_async1(ra, wA, barV_r);
          st_async1(ra + 16, wB, barV_r);
          __syncwarp();
          if (lane == 0) { if (wg == 0 && warp == 0) mbar_arrive_tx(barV, 1536); else mbar_arrive(barV); }
        }
        mbar_wait(barV, t & 1);
        float z[2][4];
#pragma unroll
        for (int T = 0; T < 2; T++) { z[T][0] = z[T][1] = z[T][2] = z[T][3] = 0.f; }
#pragma unroll
        for (int kp = 0; kp < 6; kp++) {
          uint32_t b0, b1, b2, b3;
          ldsm_x4(b0, b1, b2, b3, vbaddr + kp * 64);
#pragma unroll
          for (int T = 0; T < 2; T++) mma_bf16(z[T], WO[T][2 * kp][0], WO[T][2 * kp][1], WO[T][2 * kp][2], WO[T][2 * kp][3], b0, b1);
#pragma unroll
          for (int T = 0; T < 2; T++) mma_bf16(z[T], WO[T][2 * kp + 1][0], WO[T][2 * kp + 1][1], WO[T][2 * kp + 1][2], WO[T][2 * kp + 1][3], b2, b3);
        }
        const uint32_t tag = t + 1;
#pragma unroll
        for (int T = 0; T < 2; T++) {
          int slab = 20 * rank + 4 * (2 * wg + T) + warp;
          st_rlx4(&g_z[t & 1][slab][h][lane * 4], to_tf32(z[T][0]) | tag, to_tf32(z[T][2]) | tag, to_tf32(z[T][1]) | tag, to_tf32(z[T][3]) | tag);
        }
      }
    } else {
      asm volatile("setmaxnreg.dec.sync.aligned.u32 104;");
#pragma unroll
      for (int r = 0; r < 2; r++) {
        stage_v(r);
        __syncthreads();
        __syncthreads();
        stage_o(r);
        __syncthreads();
        __syncthreads();
      }
      const int vidx = h * 2 + rank;
      const bool reducer = vidx < 40;
      const int slabR = vidx;
      auto load_B = [&](int t) {
        const uint32_t* src = g_B + ((size_t)t * 40 + slabR) * (32 * 256);
#pragma unroll
        for (int i = 0; i < 16; i++) {
          int idx = wt + 128 * i;
          cp_async16(smem_u32(&sm.Bst[t & 1][0][0][0]) + idx * 16, src + idx * 4);
        }
        cp_async_commit();
      };
      if (reducer) load_B(0);
      const uint32_t baddr = smem_u32(&sm.mem[lane & 7][384 + (lane >> 3) * 8]);
      const uint32_t wv0 = smem_u32(&sm.wv2[(lane & 7) + ((lane >> 4) & 1) * 8][warp * 16 + ((lane >> 3) & 1) * 8]);
      const uint32_t wv1 = smem_u32(&sm.wv2[(lane & 7) + ((lane >> 4) & 1) * 8][64 + (warp & 1) * 16 + ((lane >> 3) & 1) * 8]);
      const uint32_t woa = smem_u32(&sm.wo2[(lane & 7) + ((lane >> 4) & 1) * 8][warp * 16 + ((lane >> 3) & 1) * 8]);

      auto xrows = [&](int tau) {
        const uint32_t phase = ((((tau >> 1) & 1) ^ 1) != 0) ? 0x80008000u : 0u;
        float acc[4][4];
#pragma unroll
        for (int j = 0; j < 4; j++) { acc[j][0] = acc[j][1] = acc[j][2] = acc[j][3] = 0.f; }
#pragma unroll 1
        for (int hh = 0; hh < 8; hh++) {
          const int hd = warp * 8 + hh;
          uint4 z = ld_rlx4(&g_z[tau & 1][slabR][hd][lane * 4]);
          uint4 px[4]; uint32_t pm[4];
#pragma unroll
          for (int j = 0; j < 4; j++) {
            px[j] = ld_rlx4(&g_p[tau & 1][1 + j][hd][lane * 4]);
            pm[j] = ld_rlx1(&g_p[tau & 1][1 + j][hd][128 + lane]);
          }
          uint4 B0 = *reinterpret_cast<const uint4*>(&sm.Bst[tau & 1][hd][0][lane * 4]);
          uint4 B1 = *reinterpret_cast<const uint4*>(&sm.Bst[tau & 1][hd][1][lane * 4]);
#pragma unroll
          for (int j = 0; j < 4; j++) {
            int guard = 0;
            while ((((px[j].x ^ phase) | (px[j].y ^ phase) | (px[j].z ^ phase) | (px[j].w ^ phase)) & 0x80008000u) != 0) {
              px[j] = ld_rlx4(&g_p[tau & 1][1 + j][hd][lane * 4]);
              if (++guard > SPIN_LIMIT) { g_err = 3; break; }
            }
            guard = 0;
            while (((pm[j] ^ phase) & 0x80008000u) != 0) {
              pm[j] = ld_rlx1(&g_p[tau & 1][1 + j][hd][128 + lane]);
              if (++guard > SPIN_LIMIT) { g_err = 3; break; }
            }
            uint32_t m = pm[j] & 0x7fff7fffu;
            mma_tf32(acc[j], z.x, z.y, z.z, z.w, m << 16, m & 0xffff0000u);
            mma_bf16(acc[j], B0.x, B0.y, B0.z, B0.w, px[j].x & 0x7fff7fffu, px[j].y & 0x7fff7fffu);
            mma_bf16(acc[j], B1.x, B1.y, B1.z, B1.w, px[j].z & 0x7fff7fffu, px[j].w & 0x7fff7fffu);
          }
        }
#pragma unroll
        for (int j = 0; j < 4; j++) sts4(&sm.red[warp][1 + j][lane * 4], acc[j]);
        bar_sync(6, 128);
        {
          int row = wt >> 2, c0 = (wt & 3) * 4;
          float s[4];
#pragma unroll
          for (int c = 0; c < 4; c++) {
            int col = c0 + c;
            int li = ((col & 7) * 4 + ((row & 7) >> 1)) * 4 + (col >> 3) * 2 + (row & 1);
            int qt = 1 + (row >> 3);
            s[c] = sm.red[0][qt][li] + sm.red[1][qt][li] + sm.red[2][qt][li] + sm.red[3][qt][li];
          }
          size_t off = (size_t)(tau * 32 + row) * 640 + slabR * 16 + c0;
          uint2 xv = *reinterpret_cast<const uint2*>(P.x + off);
          uint2 gv = *reinterpret_cast<const uint2*>(g_gate + off);
          float x0 = __uint_as_float(xv.x << 16), x1 = __uint_as_float(xv.x & 0xffff0000u), x2 = __uint_as_float(xv.y << 16), x3 = __uint_as_float(xv.y & 0xffff0000u);
          float g0 = __uint_as_float(gv.x << 16), g1 = __uint_as_float(gv.x & 0xffff0000u), g2 = __uint_as_float(gv.y << 16), g3 = __uint_as_float(gv.y & 0xffff0000u);
          uint2 o;
          o.x = pack_bf16(x0 + bf16r(bf16r(s[0]) * g0), x1 + bf16r(bf16r(s[1]) * g1));
          o.y = pack_bf16(x2 + bf16r(bf16r(s[2]) * g2), x3 + bf16r(bf16r(s[3]) * g3));
          *reinterpret_cast<uint2*>(P.out + off) = o;
        }
        bar_sync(6, 128);
      };

      for (int t = 0; t < NSEG; t++) {
        poll_mem<64>(g_mem[t & 1], t + 1, 384, &sm.mem[0][0], wt);
        bar_sync(3, 128);
        float a0[4] = {0.f, 0.f, 0.f, 0.f}, a0b[4] = {0.f, 0.f, 0.f, 0.f}, a1[4] = {0.f, 0.f, 0.f, 0.f};
#pragma unroll
        for (int kp = 0; kp < 8; kp++) {
          uint32_t b0, b1, b2, b3, w0, w1, w2, w3;
          ldsm_x4(b0, b1, b2, b3, baddr + kp * 64);
          ldsm_x4_t(w0, w1, w2, w3, wv0 + (2 * kp) * 16 * 208);
          mma_bf16(a0, w0, w1, w2, w3, b0, b1);
          ldsm_x4_t(w0, w1, w2, w3, wv0 + (2 * kp + 1) * 16 * 208);
          mma_bf16(a0b, w0, w1, w2, w3, b2, b3);
          if ((kp < 4) == (warp < 2)) {
            ldsm_x4_t(w0, w1, w2, w3, wv1 + (2 * kp) * 16 * 208);
            mma_bf16(a1, w0, w1, w2, w3, b0, b1);
            ldsm_x4_t(w0, w1, w2, w3, wv1 + (2 * kp + 1) * 16 * 208);
            mma_bf16(a1, w0, w1, w2, w3, b2, b3);
          }
        }
#pragma unroll
        for (int i = 0; i < 4; i++) a0[i] += a0b[i];
        sts4(&sm.pT0[2][wt][0], a0);
        sts4(&sm.pT1[2][wt][0], a1);
        bar_sync(4, 384);
        mbar_wait(barV, t & 1);
        {
          float z[4] = {0.f, 0.f, 0.f, 0.f}, zb[4] = {0.f, 0.f, 0.f, 0.f};
#pragma unroll
          for (int kp = 0; kp < 6; kp++) {
            uint32_t b0, b1, b2, b3, w0, w1, w2, w3;
            ldsm_x4(b0, b1, b2, b3, vbaddr + kp * 64);
            ldsm_x4_t(w0, w1, w2, w3, woa + (2 * kp) * 16 * 144);
            mma_bf16(z, w0, w1, w2, w3, b0, b1);
            ldsm_x4_t(w0, w1, w2, w3, woa + (2 * kp + 1) * 16 * 144);
            mma_bf16(zb, w0, w1, w2, w3, b2, b3);
          }
          const uint32_t tag = t + 1;
          int slab = 20 * rank + 16 + warp;
          st_rlx4(&g_z[t & 1][slab][h][lane * 4], to_tf32(z[0] + zb[0]) | tag, to_tf32(z[2] + zb[2]) | tag, to_tf32(z[1] + zb[1]) | tag, to_tf32(z[3] + zb[3]) | tag);
        }
        if (reducer) {
          if (t > 0) xrows(t - 1);
          cp_async_wait0();
          bar_sync(6, 128);
          if (t + 1 < NSEG) load_B(t + 1);
          const uint32_t phase = ((((t >> 1) & 1) ^ 1) != 0) ? 0x80008000u : 0u;
          const uint32_t tag = t + 1;
          float acc[4] = {0.f, 0.f, 0.f, 0.f}, acc2[4] = {0.f, 0.f, 0.f, 0.f};
          uint4 z[8], px[8]; uint32_t pm[8];
#pragma unroll
          for (int hh = 0; hh < 8; hh++) {
            const int hd = warp * 8 + hh;
            z[hh] = ld_rlx4(&g_z[t & 1][slabR][hd][lane * 4]);
            px[hh] = ld_rlx4(&g_p[t & 1][0][hd][lane * 4]);
            pm[hh] = ld_rlx1(&g_p[t & 1][0][hd][128 + lane]);
          }
#pragma unroll
          for (int hh = 0; hh < 8; hh++) {
            const int hd = warp * 8 + hh;
            int guard = 0;
            while ((((z[hh].x ^ tag) | (z[hh].y ^ tag) | (z[hh].z ^ tag) | (z[hh].w ^ tag)) & 0x1fffu) != 0) {
              z[hh] = ld_rlx4(&g_z[t & 1][slabR][hd][lane * 4]);
              if (++guard > SPIN_LIMIT) { g_err = 4; break; }
            }
            guard = 0;
            while ((((px[hh].x ^ phase) | (px[hh].y ^ phase) | (px[hh].z ^ phase) | (px[hh].w ^ phase)) & 0x80008000u) != 0) {
              px[hh] = ld_rlx4(&g_p[t & 1][0][hd][lane * 4]);
              if (++guard > SPIN_LIMIT) { g_err = 5; break; }
            }
            guard = 0;
            while (((pm[hh] ^ phase) & 0x80008000u) != 0) {
              pm[hh] = ld_rlx1(&g_p[t & 1][0][hd][128 + lane]);
              if (++guard > SPIN_LIMIT) { g_err = 5; break; }
            }
            uint4 B0 = *reinterpret_cast<const uint4*>(&sm.Bst[t & 1][hd][0][lane * 4]);
            uint4 B1 = *reinterpret_cast<const uint4*>(&sm.Bst[t & 1][hd][1][lane * 4]);
            uint32_t m = pm[hh] & 0x7fff7fffu;
            mma_tf32(acc, z[hh].x, z[hh].y, z[hh].z, z[hh].w, m << 16, m & 0xffff0000u);
            mma_bf16(acc2, B0.x, B0.y, B0.z, B0.w, px[hh].x & 0x7fff7fffu, px[hh].y & 0x7fff7fffu);
            mma_bf16(acc, B1.x, B1.y, B1.z, B1.w, px[hh].z & 0x7fff7fffu, px[hh].w & 0x7fff7fffu);
          }
#pragma unroll
          for (int i = 0; i < 4; i++) acc[i] += acc2[i];
          sts4(&sm.red[warp][0][lane * 4], acc);
          bar_sync(6, 128);
          {
            int row = wt >> 4, col = wt & 15;
            int li = ((col & 7) * 4 + (row >> 1)) * 4 + (col >> 3) * 2 + (row & 1);
            float s = sm.red[0][0][li] + sm.red[1][0][li] + sm.red[2][0][li] + sm.red[3][0][li];
            uint32_t bits = __bfloat16_as_ushort(__float2bfloat16_rn(s));
            st_rlx1(&g_mem[(t + 1) & 1][row * 640 + slabR * 16 + col], (bits << 16) | (uint32_t)(t + 2));
          }
        }
      }
      if (reducer) xrows(NSEG - 1);
    }
  }
  cluster_sync();
}

extern "C" void kernel_launch(void* const* d_in, const int* in_sizes, int n_in, void* d_out, int out_size) {
  const bf16* x = (const bf16*)d_in[0];
  const bf16* mem0 = (const bf16*)d_in[1];
  const bf16* Wq = (const bf16*)d_in[2];
  const bf16* Wk = (const bf16*)d_in[3];
  const bf16* Wv = (const bf16*)d_in[4];
  const bf16* Wo = (const bf16*)d_in[5];
  const bf16* w1 = (const bf16*)d_in[8];
  const bf16* b1 = (const bf16*)d_in[9];
  const bf16* w2 = (const bf16*)d_in[10];
  const bf16* b2 = (const bf16*)d_in[11];
  bf16* out = (bf16*)d_out;
  cudaStream_t st = cudaStreamPerThread;

  static bool init = false;
  static bf16 *p_xn, *p_y, *p_hmid, *p_gate, *p_qkv, *p_Bp;
  if (!init) {
    cudaFuncSetAttribute(chain_kernel, cudaFuncAttributeMaxDynamicSharedMemorySize, CHAIN_SMEM);
    cudaGetSymbolAddress((void**)&p_xn, g_xn);
    cudaGetSymbolAddress((void**)&p_y, g_y);
    cudaGetSymbolAddress((void**)&p_hmid, g_hmid);
    cudaGetSymbolAddress((void**)&p_gate, g_gate);
    cudaGetSymbolAddress((void**)&p_qkv, g_qkv);
    cudaGetSymbolAddress((void**)&p_Bp, g_Bplain);
    init = true;
  }
  ln_kernel<<<256, 256, 0, st>>>(x, mem0);
  gemm_kernel<1><<<dim3(12, 16, 1), 256, 0, st>>>(p_y, 640, 0, w1, 1536, 0, p_hmid, 1536, 0, b1, 640);
  gemm_kernel<2><<<dim3(5, 16, 1), 256, 0, st>>>(p_hmid, 1536, 0, w2, 640, 0, p_gate, 640, 0, b2, 1536);
  gemm_kernel<0><<<dim3(48, 16, 1), 256, 0, st>>>(p_xn, 640, 0, Wq, 6144, 0, p_qkv, 6144, 0, nullptr, 640);
  gemm_kernel<0><<<dim3(48, 16, 1), 256, 0, st>>>(p_xn, 640, 0, Wk, 6144, 0, p_qkv + (size_t)S_ * 6144, 6144, 0, nullptr, 640);
  gemm_kernel<0><<<dim3(48, 16, 1), 256, 0, st>>>(p_xn, 640, 0, Wv, 6144, 0, p_qkv + (size_t)2 * S_ * 6144, 6144, 0, nullptr, 640);
  gemm_kernel<0><<<dim3(5, 16, 32), 256, 0, st>>>(p_qkv + (size_t)2 * S_ * 6144, 6144, 192, Wo, 640, 192 * 640, p_Bp, 640, (long long)S_ * 640, nullptr, 192);
  repackB_kernel<<<(64 * 40 * 32 * 2 * 128) / 256, 256, 0, st>>>();
  ChainParams P{Wq, Wk, Wv, Wo, x, out};
  chain_kernel<<<128, 384, CHAIN_SMEM, st>>>(P);
}
```

```cpp
#include <cuda_runtime.h>
#include <cuda_bf16.h>
#include <stdint.h>

typedef __nv_bfloat16 bf16;

constexpr int S_ = 2048, D_ = 640, H_ = 32, DH_ = 192, NSEG = 64, F_ = 1536;
constexpr int SPIN_LIMIT = 1 << 20;
constexpr uint32_t CANARY = 0xFFFFFFFFu;

__device__ uint4 g_xnT[64 * 2560];
__device__ bf16 g_y[S_ * D_];
__device__ bf16 g_hmid[S_ * F_];
__device__ bf16 g_gate[S_ * D_];
__device__ bf16 g_ox[S_ * 6144];
__device__ uint4 g_B4[4 * 40 * 32 * 64];
__device__ uint4 g_mem4[4 * 640];
__device__ uint4 g_p4[4 * 5 * 32 * 40];
__device__ uint4 g_z4[4 * 40 * 32 * 16];
__device__ uint32_t g_cntB[64];
__device__ int g_err;
#define g_B ((uint32_t*)g_B4)
#define g_mem ((uint32_t*)g_mem4)
#define g_p ((uint32_t*)g_p4)
#define g_z ((uint32_t*)g_z4)
#define TR(slot) do {} while (0)

__device__ __forceinline__ uint32_t smem_u32(const void* p) { return (uint32_t)__cvta_generic_to_shared(p); }
__device__ __forceinline__ void ldsm_x4(uint32_t& r0, uint32_t& r1, uint32_t& r2, uint32_t& r3, uint32_t addr) {
  asm volatile("ldmatrix.sync.aligned.m8n8.x4.shared.b16 {%0,%1,%2,%3}, [%4];" : "=r"(r0), "=r"(r1), "=r"(r2), "=r"(r3) : "r"(addr));
}
__device__ __forceinline__ void ldsm_x4_t(uint32_t& r0, uint32_t& r1, uint32_t& r2, uint32_t& r3, uint32_t addr) {
  asm volatile("ldmatrix.sync.aligned.m8n8.x4.trans.shared.b16 {%0,%1,%2,%3}, [%4];" : "=r"(r0), "=r"(r1), "=r"(r2), "=r"(r3) : "r"(addr));
}
__device__ __forceinline__ void mma_bf16(float* c, uint32_t a0, uint32_t a1, uint32_t a2, uint32_t a3, uint32_t b0, uint32_t b1) {
  asm("mma.sync.aligned.m16n8k16.row.col.f32.bf16.bf16.f32 {%0,%1,%2,%3}, {%4,%5,%6,%7}, {%8,%9}, {%0,%1,%2,%3};"
      : "+f"(c[0]), "+f"(c[1]), "+f"(c[2]), "+f"(c[3]) : "r"(a0), "r"(a1), "r"(a2), "r"(a3), "r"(b0), "r"(b1));
}
__device__ __forceinline__ void mma_bf16_k8(float* c, uint32_t a0, uint32_t a1, uint32_t b0) {
  asm("mma.sync.aligned.m16n8k8.row.col.f32.bf16.bf16.f32 {%0,%1,%2,%3}, {%4,%5}, {%6}, {%0,%1,%2,%3};"
      : "+f"(c[0]), "+f"(c[1]), "+f"(c[2]), "+f"(c[3]) : "r"(a0), "r"(a1), "r"(b0));
}
__device__ __forceinline__ void cp_async16(uint32_t dst, const void* src) {
  asm volatile("cp.async.cg.shared.global [%0], [%1], 16;" :: "r"(dst), "l"(src) : "memory");
}
__device__ __forceinline__ void cp_async_commit() { asm volatile("cp.async.commit_group;" ::: "memory"); }
__device__ __forceinline__ void cp_async_wait0() { asm volatile("cp.async.wait_group 0;" ::: "memory"); }
__device__ __forceinline__ void bar_sync(int id, int n) { asm volatile("bar.sync %0, %1;" :: "r"(id), "r"(n) : "memory"); }
__device__ __forceinline__ void bar_arrive(int id, int n) { asm volatile("bar.arrive %0, %1;" :: "r"(id), "r"(n) : "memory"); }
__device__ __forceinline__ uint4 ld_rlx4(const uint32_t* p) {
  uint4 v;
  asm volatile("ld.relaxed.gpu.global.v4.u32 {%0,%1,%2,%3}, [%4];" : "=r"(v.x), "=r"(v.y), "=r"(v.z), "=r"(v.w) : "l"(p) : "memory");
  return v;
}
__device__ __forceinline__ uint2 ld_rlx2(const uint32_t* p) {
  uint2 v;
  asm volatile("ld.relaxed.gpu.global.v2.u32 {%0,%1}, [%2];" : "=r"(v.x), "=r"(v.y) : "l"(p) : "memory");
  return v;
}
__device__ __forceinline__ uint32_t ld_rlx1(const uint32_t* p) {
  uint32_t v;
  asm volatile("ld.relaxed.gpu.global.u32 %0, [%1];" : "=r"(v) : "l"(p) : "memory");
  return v;
}
__device__ __forceinline__ uint32_t ld_acq1(const uint32_t* p) {
  uint32_t v;
  asm volatile("ld.acquire.gpu.global.u32 %0, [%1];" : "=r"(v) : "l"(p) : "memory");
  return v;
}
__device__ __forceinline__ void st_rlx4(uint32_t* p, uint32_t a, uint32_t b, uint32_t c, uint32_t d) {
  asm volatile("st.relaxed.gpu.global.v4.u32 [%0], {%1,%2,%3,%4};" :: "l"(p), "r"(a), "r"(b), "r"(c), "r"(d) : "memory");
}
__device__ __forceinline__ void st_rlx2(uint32_t* p, uint32_t a, uint32_t b) {
  asm volatile("st.relaxed.gpu.global.v2.u32 [%0], {%1,%2};" :: "l"(p), "r"(a), "r"(b) : "memory");
}
__device__ __forceinline__ void st_rlx1(uint32_t* p, uint32_t a) {
  asm volatile("st.relaxed.gpu.global.u32 [%0], %1;" :: "l"(p), "r"(a) : "memory");
}
__device__ __forceinline__ void sts1(uint32_t addr, uint32_t a) { asm volatile("st.shared.u32 [%0], %1;" :: "r"(addr), "r"(a) : "memory"); }
__device__ __forceinline__ void sts1f(uint32_t addr, float a) { asm volatile("st.shared.f32 [%0], %1;" :: "r"(addr), "f"(a) : "memory"); }
__device__ __forceinline__ void sts2f(uint32_t addr, float a, float b) { asm volatile("st.shared.v2.f32 [%0], {%1,%2};" :: "r"(addr), "f"(a), "f"(b) : "memory"); }
__device__ __forceinline__ void sts4(uint32_t addr, uint32_t a, uint32_t b, uint32_t c, uint32_t d) {
  asm volatile("st.shared.v4.u32 [%0], {%1,%2,%3,%4};" :: "r"(addr), "r"(a), "r"(b), "r"(c), "r"(d) : "memory");
}
__device__ __forceinline__ void sts4f(uint32_t addr, float a, float b, float c, float d) {
  asm volatile("st.shared.v4.f32 [%0], {%1,%2,%3,%4};" :: "r"(addr), "f"(a), "f"(b), "f"(c), "f"(d) : "memory");
}
__device__ __forceinline__ uint32_t lds1(uint32_t addr) { uint32_t v; asm volatile("ld.shared.u32 %0, [%1];" : "=r"(v) : "r"(addr)); return v; }
__device__ __forceinline__ float2 lds2f(uint32_t addr) { float2 v; asm volatile("ld.shared.v2.f32 {%0,%1}, [%2];" : "=f"(v.x), "=f"(v.y) : "r"(addr)); return v; }
__device__ __forceinline__ uint4 lds4(uint32_t addr) {
  uint4 v; asm volatile("ld.shared.v4.u32 {%0,%1,%2,%3}, [%4];" : "=r"(v.x), "=r"(v.y), "=r"(v.z), "=r"(v.w) : "r"(addr)); return v;
}
__device__ __forceinline__ float4 lds4f(uint32_t addr) {
  float4 v; asm volatile("ld.shared.v4.f32 {%0,%1,%2,%3}, [%4];" : "=f"(v.x), "=f"(v.y), "=f"(v.z), "=f"(v.w) : "r"(addr)); return v;
}
__device__ __forceinline__ void mbar_init(uint32_t bar, int count) {
  asm volatile("mbarrier.init.shared::cta.b64 [%0], %1;" :: "r"(bar), "r"(count) : "memory");
}
__device__ __forceinline__ void mbar_arrive(uint32_t bar) {
  asm volatile("mbarrier.arrive.shared::cta.b64 _, [%0];" :: "r"(bar) : "memory");
}
__device__ __forceinline__ void mbar_arrive_remote(uint32_t bar) {
  asm volatile("mbarrier.arrive.release.cluster.shared::cluster.b64 _, [%0];" :: "r"(bar) : "memory");
}
__device__ __forceinline__ void mbar_arrive_tx(uint32_t bar, uint32_t tx) {
  asm volatile("mbarrier.arrive.expect_tx.shared::cta.b64 _, [%0], %1;" :: "r"(bar), "r"(tx) : "memory");
}
__device__ __forceinline__ void mbar_wait(uint32_t bar, uint32_t parity) {
  uint32_t done = 0;
  int guard = 0;
  while (true) {
    asm volatile("{\n.reg .pred p;\nmbarrier.try_wait.parity.acquire.cluster.shared::cta.b64 p, [%1], %2;\nselp.u32 %0, 1, 0, p;\n}"
                 : "=r"(done) : "r"(bar), "r"(parity) : "memory");
    if (done) break;
    if (++guard > SPIN_LIMIT) { g_err = 1; break; }
  }
}
__device__ __forceinline__ uint32_t mapa(uint32_t addr, uint32_t rank) {
  uint32_t r;
  asm volatile("mapa.shared::cluster.u32 %0, %1, %2;" : "=r"(r) : "r"(addr), "r"(rank));
  return r;
}
__device__ __forceinline__ void st_async1(uint32_t addr, uint32_t v, uint32_t bar) {
  asm volatile("st.async.weak.shared::cluster.mbarrier::complete_tx::bytes.b32 [%0], %1, [%2];" :: "r"(addr), "r"(v), "r"(bar) : "memory");
}
__device__ __forceinline__ void st_async2(uint32_t addr, float a, float b, uint32_t bar) {
  asm volatile("st.async.weak.shared::cluster.mbarrier::complete_tx::bytes.v2.f32 [%0], {%1,%2}, [%3];" :: "r"(addr), "f"(a), "f"(b), "r"(bar) : "memory");
}
__device__ __forceinline__ void st_async4(uint32_t addr, float a, float b, float c, float d, uint32_t bar) {
  asm volatile("st.async.weak.shared::cluster.mbarrier::complete_tx::bytes.v4.f32 [%0], {%1,%2,%3,%4}, [%5];" :: "r"(addr), "f"(a), "f"(b), "f"(c), "f"(d), "r"(bar) : "memory");
}
__device__ __forceinline__ void cluster_sync() {
  asm volatile("barrier.cluster.arrive.release.aligned;\nbarrier.cluster.wait.acquire.aligned;" ::: "memory");
}
__device__ __forceinline__ void fence_async_smem() { asm volatile("fence.proxy.async.shared::cta;" ::: "memory"); }
__device__ __forceinline__ void fence_async_all() { asm volatile("fence.proxy.async;" ::: "memory"); }
__device__ __forceinline__ void bulk_g2s(uint32_t dst, const void* src, uint32_t bytes, uint32_t bar) {
  asm volatile("cp.async.bulk.shared::cluster.global.mbarrier::complete_tx::bytes [%0], [%1], %2, [%3];"
               :: "r"(dst), "l"(src), "r"(bytes), "r"(bar) : "memory");
}
__device__ __forceinline__ void bulk_g2s_mc(uint32_t dst, const void* src, uint32_t bytes, uint32_t bar, uint16_t mask) {
  asm volatile("cp.async.bulk.shared::cluster.global.mbarrier::complete_tx::bytes.multicast::cluster [%0], [%1], %2, [%3], %4;"
               :: "r"(dst), "l"(src), "r"(bytes), "r"(bar), "h"(mask) : "memory");
}
__device__ __forceinline__ void bulk_s2s(uint32_t dst_remote, uint32_t src, uint32_t bytes, uint32_t bar_remote) {
  asm volatile("cp.async.bulk.shared::cluster.shared::cta.mbarrier::complete_tx::bytes [%0], [%1], %2, [%3];"
               :: "r"(dst_remote), "r"(src), "r"(bytes), "r"(bar_remote) : "memory");
}
__device__ __forceinline__ float bf16r(float x) { return __bfloat162float(__float2bfloat16_rn(x)); }
__device__ __forceinline__ uint32_t pack_bf16(float lo, float hi) {
  uint32_t r;
  asm("cvt.rn.bf16x2.f32 %0, %1, %2;" : "=r"(r) : "f"(hi), "f"(lo));
  return r;
}
__device__ __forceinline__ uint64_t mkdesc(uint32_t saddr, uint32_t lbo, uint32_t sbo, int swz) {
  uint64_t d = 0;
  d |= (uint64_t)((saddr & 0x3FFFF) >> 4);
  d |= (uint64_t)((lbo & 0x3FFFF) >> 4) << 16;
  d |= (uint64_t)((sbo & 0x3FFFF) >> 4) << 32;
  d |= (uint64_t)swz << 62;
  return d;
}
#define WG_FENCE() asm volatile("wgmma.fence.sync.aligned;" ::: "memory")
#define WG_COMMIT() asm volatile("wgmma.commit_group.sync.aligned;" ::: "memory")
#define WG_WAIT0() asm volatile("wgmma.wait_group.sync.aligned 0;" ::: "memory")
template <int TB>
__device__ __forceinline__ void rs32(float* d, const uint32_t* a, uint64_t b) {
  asm volatile("wgmma.mma_async.sync.aligned.m64n32k16.f32.bf16.bf16 {%0,%1,%2,%3,%4,%5,%6,%7,%8,%9,%10,%11,%12,%13,%14,%15}, {%16,%17,%18,%19}, %20, 1, 1, 1, %21;"
    : "+f"(d[0]), "+f"(d[1]), "+f"(d[2]), "+f"(d[3]), "+f"(d[4]), "+f"(d[5]), "+f"(d[6]), "+f"(d[7]),
      "+f"(d[8]), "+f"(d[9]), "+f"(d[10]), "+f"(d[11]), "+f"(d[12]), "+f"(d[13]), "+f"(d[14]), "+f"(d[15])
    : "r"(a[0]), "r"(a[1]), "r"(a[2]), "r"(a[3]), "l"(b), "n"(TB));
}
template <int TA, int TB>
__device__ __forceinline__ void ss32(float* d, uint64_t a, uint64_t b) {
  asm volatile("wgmma.mma_async.sync.aligned.m64n32k16.f32.bf16.bf16 {%0,%1,%2,%3,%4,%5,%6,%7,%8,%9,%10,%11,%12,%13,%14,%15}, %16, %17, 1, 1, 1, %18, %19;"
    : "+f"(d[0]), "+f"(d[1]), "+f"(d[2]), "+f"(d[3]), "+f"(d[4]), "+f"(d[5]), "+f"(d[6]), "+f"(d[7]),
      "+f"(d[8]), "+f"(d[9]), "+f"(d[10]), "+f"(d[11]), "+f"(d[12]), "+f"(d[13]), "+f"(d[14]), "+f"(d[15])
    : "l"(a), "l"(b), "n"(TA), "n"(TB));
}

__device__ __forceinline__ void ln_row(const float (&v)[20], float (&o)[20]) {
  float s = 0.f;
#pragma unroll
  for (int i = 0; i < 20; i++) s += v[i];
#pragma unroll
  for (int m = 16; m; m >>= 1) s += __shfl_xor_sync(0xffffffffu, s, m);
  float mean = s * (1.f / 640.f);
  float q = 0.f;
#pragma unroll
  for (int i = 0; i < 20; i++) { float d = v[i] - mean; q += d * d; }
#pragma unroll
  for (int m = 16; m; m >>= 1) q += __shfl_xor_sync(0xffffffffu, q, m);
  float var = bf16r(q * (1.f / 640.f));
  float mb = bf16r(mean);
  float den = bf16r(sqrtf(bf16r(var + 1e-5f)));
#pragma unroll
  for (int i = 0; i < 20; i++) o[i] = bf16r(bf16r(v[i] - mb) / den);
}

__global__ void __launch_bounds__(256) ln_kernel(const bf16* __restrict__ x, const bf16* __restrict__ mem0) {
  const int gtid = blockIdx.x * 256 + threadIdx.x;
  int warp = gtid >> 5, lane = threadIdx.x & 31;
  if (gtid < 2560) {
    uint32_t w = reinterpret_cast<const uint32_t*>(mem0)[gtid];
    if ((w & 0xffffu) == 0xffffu) w = (w & 0xffff0000u) | 0x7fffu;
    g_mem[gtid] = w;
  } else if (gtid < 10240) {
    g_mem[gtid] = CANARY;
  } else if (gtid < 10240 + 64) {
    g_cntB[gtid - 10240] = 0;
  }
  for (int i = gtid; i < 4 * 40 * 32 * 16; i += 65536) g_z4[i] = make_uint4(CANARY, CANARY, CANARY, CANARY);
  if (warp >= S_) return;
  const uint32_t* xr = reinterpret_cast<const uint32_t*>(x + (size_t)warp * D_);
  float v[20], o[20], o2[20];
#pragma unroll
  for (int i = 0; i < 10; i++) {
    uint32_t w = xr[i * 32 + lane];
    v[2 * i] = __uint_as_float(w << 16);
    v[2 * i + 1] = __uint_as_float(w & 0xffff0000u);
  }
  ln_row(v, o);
  ln_row(o, o2);
  const int seg = warp >> 5, r = warp & 31;
  uint32_t* xo = reinterpret_cast<uint32_t*>(g_xnT) + seg * 10240 + r * 32 + (((lane >> 2) ^ (r & 7)) << 2) + (lane & 3);
  uint32_t* yo = reinterpret_cast<uint32_t*>(g_y + (size_t)warp * D_);
#pragma unroll
  for (int i = 0; i < 10; i++) {
    xo[i * 1024] = pack_bf16(o[2 * i], o[2 * i + 1]);
    yo[i * 32 + lane] = pack_bf16(o2[2 * i], o2[2 * i + 1]);
  }
}

template <int EPI>
__global__ void __launch_bounds__(256) gemm_kernel(const bf16* __restrict__ A, int lda, long long sA,
                                                   const bf16* __restrict__ B, int ldb, long long sB,
                                                   bf16* __restrict__ C, int ldc, long long sC,
                                                   const bf16* __restrict__ bias, int K,
                                                   const bf16* __restrict__ xin = nullptr, const bf16* __restrict__ gate = nullptr) {
  constexpr int BM = 128, BN = 128, BK = 32;
  __shared__ __align__(16) bf16 As[2][BM][BK + 8];
  __shared__ __align__(16) bf16 Bs[2][BK][BN + 8];
  A += sA * blockIdx.z; B += sB * blockIdx.z; C += sC * blockIdx.z;
  int tid = threadIdx.x, warp = tid >> 5, lane = tid & 31;
  int m0 = blockIdx.y * BM, n0 = blockIdx.x * BN;
  int wm = (warp >> 2) * 64, wn = (warp & 3) * 32;
  float acc[4][4][4];
#pragma unroll
  for (int i = 0; i < 4; i++)
#pragma unroll
    for (int j = 0; j < 4; j++)
#pragma unroll
      for (int k = 0; k < 4; k++) acc[i][j][k] = 0.f;
  auto load = [&](int buf, int k0) {
#pragma unroll
    for (int i = 0; i < 2; i++) {
      int idx = tid + i * 256;
      int r = idx >> 2, c = (idx & 3) * 8;
      cp_async16(smem_u32(&As[buf][r][c]), A + (size_t)(m0 + r) * lda + k0 + c);
      int r2 = idx >> 4, c2 = (idx & 15) * 8;
      cp_async16(smem_u32(&Bs[buf][r2][c2]), B + (size_t)(k0 + r2) * ldb + n0 + c2);
    }
    cp_async_commit();
  };
  load(0, 0);
  int nk = K / BK;
  for (int kt = 0; kt < nk; kt++) {
    cp_async_wait0();
    __syncthreads();
    if (kt + 1 < nk) load((kt + 1) & 1, (kt + 1) * BK);
    int buf = kt & 1;
#pragma unroll
    for (int ks = 0; ks < 2; ks++) {
      uint32_t a[4][4], b[2][4];
#pragma unroll
      for (int i = 0; i < 4; i++)
        ldsm_x4(a[i][0], a[i][1], a[i][2], a[i][3], smem_u32(&As[buf][wm + i * 16 + (lane & 15)][ks * 16 + (lane >> 4) * 8]));
#pragma unroll
      for (int j = 0; j < 2; j++)
        ldsm_x4_t(b[j][0], b[j][1], b[j][2], b[j][3], smem_u32(&Bs[buf][ks * 16 + (lane & 15)][wn + j * 16 + (lane >> 4) * 8]));
#pragma unroll
      for (int i = 0; i < 4; i++)
#pragma unroll
        for (int j = 0; j < 4; j++)
          mma_bf16(acc[i][j], a[i][0], a[i][1], a[i][2], a[i][3], b[j >> 1][(j & 1) * 2], b[j >> 1][(j & 1) * 2 + 1]);
    }
  }
  int g = lane >> 2, q = lane & 3;
#pragma unroll
  for (int i = 0; i < 4; i++)
#pragma unroll
    for (int j = 0; j < 4; j++)
#pragma unroll
      for (int hh = 0; hh < 2; hh++) {
        int r = m0 + wm + i * 16 + g + hh * 8, c = n0 + wn + j * 8 + q * 2;
        float v0 = acc[i][j][hh * 2], v1 = acc[i][j][hh * 2 + 1];
        if (EPI == 3) {
          uint32_t xv = *reinterpret_cast<const uint32_t*>(xin + (size_t)r * ldc + c);
          uint32_t gv = *reinterpret_cast<const uint32_t*>(gate + (size_t)r * ldc + c);
          v0 = __uint_as_float(xv << 16) + bf16r(bf16r(v0) * __uint_as_float(gv << 16));
          v1 = __uint_as_float(xv & 0xffff0000u) + bf16r(bf16r(v1) * __uint_as_float(gv & 0xffff0000u));
        } else if (EPI != 0) {
          v0 = bf16r(bf16r(v0) + __bfloat162float(bias[c]));
          v1 = bf16r(bf16r(v1) + __bfloat162float(bias[c + 1]));
          if (EPI == 1) {
            v0 = 0.5f * v0 * (1.f + tanhf(0.7978845608028654f * (v0 + 0.044715f * v0 * v0 * v0)));
            v1 = 0.5f * v1 * (1.f + tanhf(0.7978845608028654f * (v1 + 0.044715f * v1 * v1 * v1)));
          } else {
            v0 = v0 / (1.f + __expf(-v0));
            v1 = v1 / (1.f + __expf(-v1));
          }
        }
        *reinterpret_cast<uint32_t*>(C + (size_t)r * ldc + c) = pack_bf16(v0, v1);
      }
}

constexpr uint32_t QK_W2 = 0, QK_XN = 81920, QK_BSL = 122880, QK_QK = 155648, QK_PL = 180224, QK_MEM = 200704,
                   QK_QKM = 211072, QK_SCM = 214144, QK_SCX = 216704, QK_RED = 226944, QK_BAR = 229504, QK_END = 229632;
constexpr uint32_t VO_WO = 0, VO_XN = 98304, VO_VX = 139264, VO_MEM = 188416, VO_VM = 198784, VO_PC = 211072,
                   VO_PB = 213120, VO_BAR = 221312;
constexpr int CHAIN_SMEM = QK_END + 1024;
#define XSPLIT 22

struct ChainParams { const bf16 *Wq, *Wk, *Wv, *Wo; };
constexpr float SCALE = 0.07216878364870322f;

__device__ __forceinline__ void softmax_row(float (&s)[5][2], uint32_t (&w)[5]) {
  float m = -3.0e38f;
#pragma unroll
  for (int j = 0; j < 5; j++) m = fmaxf(m, fmaxf(s[j][0], s[j][1]));
  m = fmaxf(m, __shfl_xor_sync(0xffffffffu, m, 1));
  m = fmaxf(m, __shfl_xor_sync(0xffffffffu, m, 2));
  float sum = 0.f;
#pragma unroll
  for (int j = 0; j < 5; j++) {
    s[j][0] = __expf(s[j][0] - m); s[j][1] = __expf(s[j][1] - m);
    sum += s[j][0] + s[j][1];
  }
  sum += __shfl_xor_sync(0xffffffffu, sum, 1);
  sum += __shfl_xor_sync(0xffffffffu, sum, 2);
  float inv = __frcp_rn(sum);
#pragma unroll
  for (int j = 0; j < 5; j++) w[j] = pack_bf16(s[j][0] * inv, s[j][1] * inv);
}

__device__ __forceinline__ void poll_mem(int slot, uint32_t smem_mem, int warp, int lane) {
  const uint32_t* gm = g_mem + slot * 2560 + warp * 640;
  {
    const uint32_t* s1 = gm + lane * 8, *s2 = gm + (32 + (lane & 7)) * 8;
    int guard = 0;
    while (true) {
      uint32_t w1 = ld_rlx1(s1), w2 = ld_rlx1(s2);
      if (__all_sync(0xffffffffu, w1 != CANARY && w2 != CANARY)) break;
      if (++guard > SPIN_LIMIT) { g_err = 6; break; }
    }
  }
  uint4 v[5];
  int guard = 0;
  while (true) {
#pragma unroll
    for (int i = 0; i < 5; i++) v[i] = ld_rlx4(gm + (lane + 32 * i) * 4);
    bool bad = false;
#pragma unroll
    for (int i = 0; i < 5; i++) bad |= (v[i].x == CANARY) | (v[i].y == CANARY) | (v[i].z == CANARY) | (v[i].w == CANARY);
    if (!bad) break;
    if (++guard > SPIN_LIMIT) { g_err = 2; break; }
  }
#pragma unroll
  for (int i = 0; i < 5; i++) {
    int vi = lane + 32 * i;
    int row = 2 * warp + (vi >= 80 ? 1 : 0), c = vi >= 80 ? vi - 80 : vi;
    sts4(smem_mem + row * 1296 + c * 16, v[i].x, v[i].y, v[i].z, v[i].w);
  }
}

__device__ __forceinline__ void load_tile(uint32_t dst, int nrows, const bf16* srcA, const bf16* srcB, int ld, int tid) {
  for (int idx = tid; idx < nrows * 8; idx += 512) {
    int k = idx >> 3, c = idx & 7;
    const bf16* s = (c < 4 ? srcA + c * 8 : srcB + (c - 4) * 8) + (size_t)k * ld;
    cp_async16(dst + k * 128 + ((c ^ (k & 7)) << 4), s);
  }
}

__device__ __forceinline__ constexpr uint32_t xoff(int ks) { return (uint32_t)(((ks >> 2) * 4096 + (ks & 3) * 32) >> 4); }

__global__ void __cluster_dims__(2, 1, 1) __launch_bounds__(512, 1) chain_kernel(ChainParams P) {
  extern __shared__ uint8_t smem_raw[];
  const uint32_t sb = (smem_u32(smem_raw) + 1023u) & ~1023u;
  const int tid = threadIdx.x, wg = tid >> 7, wt = tid & 127, warp = wt >> 5, lane = tid & 31;
  const int g = lane >> 2, qi = lane & 3;
  const int b = blockIdx.x, rank = b & 1, pair = b >> 1, h = pair >> 1, type = pair & 1;
  const uint32_t a_off = ((lane & 7) + ((lane >> 4) & 1) * 8) * 128 + (((2 * warp + ((lane >> 3) & 1)) ^ (lane & 7)) << 4);

  if (type == 0) {
    const uint32_t barM = sb + QK_BAR, barX = barM + 8, xnF = barM + 16, xnE = barM + 24, barB = barM + 32;
    if (tid == 0) {
      mbar_init(barM, 4); mbar_init(barX, 4); mbar_init(xnF, 1); mbar_init(xnE, 24); mbar_init(barB, 1);
      asm volatile("fence.mbarrier_init.release.cluster;" ::: "memory");
    }
    const bf16* wq = P.Wq + h * DH_ + 96 * rank;
    const bf16* wk = P.Wk + h * DH_ + 96 * rank;
    const int qidx = h * 2 + rank;
    const bool reducer = qidx < 40;
    load_tile(sb, 640, wq, wq + 32, 6144, tid);
    load_tile(sb + 81920, 640, wq + 64, wk, 6144, tid);
    cp_async_commit();
    cluster_sync();
    const uint32_t baddr = sb + QK_MEM + (lane & 7) * 1296 + (lane >> 3) * 16;
    const uint64_t xdesc = mkdesc(sb + QK_XN, 16, 1024, 1);
    const uint32_t xnE_r = mapa(xnE, rank ^ 1);
    if (wg < 2) {
      asm volatile("setmaxnreg.inc.sync.aligned.u32 200;");
      uint32_t W[40][4];
      cp_async_wait0();
      __syncthreads();
#pragma unroll
      for (int ks = 0; ks < 40; ks++) ldsm_x4_t(W[ks][0], W[ks][1], W[ks][2], W[ks][3], sb + wg * 81920 + a_off + ks * 2048);
      __syncthreads();
      load_tile(sb, 640, wk + 32, wk + 64, 6144, tid);
      cp_async_commit();
      cluster_sync();
      if (tid == 0) {
        mbar_arrive_tx(xnF, 40960);
        bulk_g2s_mc(sb + QK_XN + rank * 20480, reinterpret_cast<const uint8_t*>(g_xnT) + rank * 20480, 20480, xnF, 3);
      }
      cp_async_wait0();
      fence_async_smem();
      __syncthreads();
      const int feat = wg * 64 + warp * 16 + g;
      for (int t = -1; t < NSEG; t++) {
        float d[16];
        if (t >= 0) {
          bar_sync(1, 512);
          if (wg == 0) TR(8);
#pragma unroll
          for (int i = 0; i < 16; i++) d[i] = 0.f;
#pragma unroll
          for (int kp = 0; kp < 20; kp++) {
            uint32_t b0, b1, b2, b3;
            ldsm_x4(b0, b1, b2, b3, baddr + kp * 64);
            mma_bf16(d + ((2 * kp) & 3) * 4, W[2 * kp][0], W[2 * kp][1], W[2 * kp][2], W[2 * kp][3], b0, b1);
            mma_bf16(d + ((2 * kp + 1) & 3) * 4, W[2 * kp + 1][0], W[2 * kp + 1][1], W[2 * kp + 1][2], W[2 * kp + 1][3], b2, b3);
          }
          sts1(sb + QK_QKM + feat * 16 + qi * 4, pack_bf16((d[0] + d[4]) + (d[8] + d[12]), (d[1] + d[5]) + (d[9] + d[13])));
          sts1(sb + QK_QKM + feat * 16 + 128 + qi * 4, pack_bf16((d[2] + d[6]) + (d[10] + d[14]), (d[3] + d[7]) + (d[11] + d[15])));
          bar_arrive(2, 512);
          if (wg == 0) TR(9);
          bar_sync(3, 512);
        }
        if (t + 1 < NSEG) {
          mbar_wait(xnF, (t + 1) & 1);
          if (wg == 0) TR(10);
#pragma unroll
          for (int i = 0; i < 16; i++) d[i] = 0.f;
          WG_FENCE();
#pragma unroll
          for (int ks = 0; ks < XSPLIT; ks++) rs32<0>(d, W[ks], xdesc + xoff(ks));
          WG_COMMIT();
          WG_WAIT0();
          if (reducer && t >= 0) { bar_arrive(4, 512); if (wg == 0) TR(11); bar_sync(5, 512); }
          WG_FENCE();
#pragma unroll
          for (int ks = XSPLIT; ks < 40; ks++) rs32<0>(d, W[ks], xdesc + xoff(ks));
          WG_COMMIT();
          WG_WAIT0();
          if (lane == 0) { mbar_arrive(xnE); mbar_arrive_remote(xnE_r); }
          const uint32_t qa = sb + QK_QK + ((t + 1) & 1) * 12288 + feat * 64 + ((qi ^ ((feat >> 1) & 3)) << 4);
          sts4(qa, pack_bf16(d[0], d[1]), pack_bf16(d[4], d[5]), pack_bf16(d[8], d[9]), pack_bf16(d[12], d[13]));
          sts4(qa + 512, pack_bf16(d[2], d[3]), pack_bf16(d[6], d[7]), pack_bf16(d[10], d[11]), pack_bf16(d[14], d[15]));
          if (wg == 0) TR(12);
          if (tid == 0 && t + 2 < NSEG) {
            mbar_wait(xnE, (t + 1) & 1);
            mbar_arrive_tx(xnF, 40960);
            bulk_g2s_mc(sb + QK_XN + rank * 20480, reinterpret_cast<const uint8_t*>(g_xnT) + (size_t)(t + 2) * 40960 + rank * 20480, 20480, xnF, 3);
          }
          __syncwarp();
        } else if (reducer) {
          bar_arrive(4, 512); bar_sync(5, 512);
        }
      }
    } else if (wg == 2) {
      asm volatile("setmaxnreg.dec.sync.aligned.u32 56;");
      cp_async_wait0();
      __syncthreads();
      __syncthreads();
      load_tile(sb, 640, wk + 32, wk + 64, 6144, tid);
      cp_async_commit();
      cluster_sync();
      cp_async_wait0();
      fence_async_smem();
      __syncthreads();
      const int feat = 128 + warp * 16 + g;
      const uint64_t wdesc = mkdesc(sb + QK_W2, 1024, 1024, 1);
      for (int t = -1; t < NSEG; t++) {
        float d[16];
        if (t >= 0) {
          bar_sync(1, 512);
#pragma unroll
          for (int i = 0; i < 16; i++) d[i] = 0.f;
#pragma unroll
          for (int kp = 0; kp < 20; kp++) {
            uint32_t b0, b1, b2, b3, a0, a1, a2, a3, c0, c1, c2, c3;
            ldsm_x4(b0, b1, b2, b3, baddr + kp * 64);
            ldsm_x4_t(a0, a1, a2, a3, sb + QK_W2 + a_off + (2 * kp) * 2048);
            ldsm_x4_t(c0, c1, c2, c3, sb + QK_W2 + a_off + (2 * kp + 1) * 2048);
            mma_bf16(d + ((2 * kp) & 3) * 4, a0, a1, a2, a3, b0, b1);
            mma_bf16(d + ((2 * kp + 1) & 3) * 4, c0, c1, c2, c3, b2, b3);
          }
          sts1(sb + QK_QKM + feat * 16 + qi * 4, pack_bf16((d[0] + d[4]) + (d[8] + d[12]), (d[1] + d[5]) + (d[9] + d[13])));
          sts1(sb + QK_QKM + feat * 16 + 128 + qi * 4, pack_bf16((d[2] + d[6]) + (d[10] + d[14]), (d[3] + d[7]) + (d[11] + d[15])));
          bar_arrive(2, 512);
          bar_sync(3, 512);
        }
        if (t + 1 < NSEG) {
          mbar_wait(xnF, (t + 1) & 1);
#pragma unroll
          for (int i = 0; i < 16; i++) d[i] = 0.f;
          WG_FENCE();
#pragma unroll
          for (int ks = 0; ks < XSPLIT; ks++) ss32<1, 0>(d, wdesc + ks * 128, xdesc + xoff(ks));
          WG_COMMIT();
          WG_WAIT0();
          if (reducer && t >= 0) { bar_arrive(4, 512); bar_sync(5, 512); }
          WG_FENCE();
#pragma unroll
          for (int ks = XSPLIT; ks < 40; ks++) ss32<1, 0>(d, wdesc + ks * 128, xdesc + xoff(ks));
          WG_COMMIT();
          WG_WAIT0();
          if (lane == 0) { mbar_arrive(xnE); mbar_arrive_remote(xnE_r); }
          const uint32_t qa = sb + QK_QK + ((t + 1) & 1) * 12288 + feat * 64 + ((qi ^ ((feat >> 1) & 3)) << 4);
          sts4(qa, pack_bf16(d[0], d[1]), pack_bf16(d[4], d[5]), pack_bf16(d[8], d[9]), pack_bf16(d[12], d[13]));
          sts4(qa + 512, pack_bf16(d[2], d[3]), pack_bf16(d[6], d[7]), pack_bf16(d[10], d[11]), pack_bf16(d[14], d[15]));
          TR(13);
        } else if (reducer) {
          bar_arrive(4, 512); bar_sync(5, 512);
        }
      }
    } else {
      asm volatile("setmaxnreg.dec.sync.aligned.u32 56;");
      cp_async_wait0();
      __syncthreads();
      __syncthreads();
      load_tile(sb, 640, wk + 32, wk + 64, 6144, tid);
      cp_async_commit();
      cluster_sync();
      cp_async_wait0();
      fence_async_smem();
      __syncthreads();
      const uint32_t barM0 = mapa(barM, 0), barX1 = mapa(barX, 1);
      const uint32_t scm_r = mapa(sb + QK_SCM + 1280 + lane * 8, 0);
      const uint32_t scx_r = mapa(sb + QK_SCX + lane * 16, 1);
      const uint32_t qm_a = sb + QK_QKM + lane * 16;
      const uint32_t swz = (lane >> 1) & 3;
      for (int t = 0; t < NSEG; t++) {
        poll_mem(t & 3, sb + QK_MEM, warp, lane);
        bar_sync(1, 512);
        TR(0);
        bool bload = false;
        if (reducer && wt == 0) {
          if (ld_acq1(&g_cntB[t]) == 128u) {
            fence_async_all();
            mbar_arrive_tx(barB, 32768);
            bulk_g2s(sb + QK_BSL, g_B + ((size_t)(t & 3) * 40 + qidx) * 8192, 32768, barB);
            bload = true;
          }
        }
        const uint32_t qkb = sb + QK_QK + (t & 1) * 12288;
        bar_sync(2, 512);
        TR(1);
        {
          float sc[8], s0[8];
#pragma unroll
          for (int i = 0; i < 8; i++) { sc[i] = 0.f; s0[i] = 0.f; }
          const uint32_t ka = qkb + (96 + lane) * 64 + ((warp ^ swz) << 4);
#pragma unroll
          for (int kb = 0; kb < 3; kb++) {
            uint32_t a0, a1, a2, a3, b0, b1, b2, b3;
            ldsm_x4_t(a0, a1, a2, a3, qm_a + kb * 512);
            ldsm_x4_t(b0, b1, b2, b3, ka + kb * 2048);
            mma_bf16(sc, a0, 0u, a1, 0u, b0, b1);
            mma_bf16(sc + 4, a2, 0u, a3, 0u, b2, b3);
            if (warp == 0) {
              ldsm_x4_t(b0, b1, b2, b3, qm_a + 1536 + kb * 512);
              mma_bf16(s0, a0, 0u, a1, 0u, b0, b1);
              mma_bf16(s0 + 4, a2, 0u, a3, 0u, b2, b3);
            }
          }
          if (rank == 0) {
            sts2f(sb + QK_SCM + (warp + 1) * 256 + lane * 8, sc[0] + sc[4], sc[1] + sc[5]);
            if (warp == 0) sts2f(sb + QK_SCM + lane * 8, s0[0] + s0[4], s0[1] + s0[5]);
            __syncwarp();
            if (lane == 0) { if (warp == 0) mbar_arrive_tx(barM, 1280); else mbar_arrive(barM); }
          } else {
            st_async2(scm_r + (warp + 1) * 256, sc[0] + sc[4], sc[1] + sc[5], barM0);
            if (warp == 0) st_async2(scm_r, s0[0] + s0[4], s0[1] + s0[5], barM0);
          }
        }
        const uint32_t phase = ((((t >> 2) & 1) ^ 1) != 0) ? 0x80008000u : 0u;
        TR(2);
        if (rank == 0 && warp == 0) {
          mbar_wait(barM, t & 1);
          float s[5][2];
#pragma unroll
          for (int j = 0; j < 5; j++) {
            float2 u = lds2f(sb + QK_SCM + j * 256 + lane * 8);
            float2 v = lds2f(sb + QK_SCM + 1280 + j * 256 + lane * 8);
            s[j][0] = bf16r(bf16r(u.x + v.x) * SCALE);
            s[j][1] = bf16r(bf16r(u.y + v.y) * SCALE);
          }
          uint32_t w[5];
          softmax_row(s, w);
          uint32_t* dst = g_p + ((size_t)((t & 3) * 5) * 32 + h) * 160;
          st_rlx4(dst + lane * 4, w[1] | phase, w[2] | phase, w[3] | phase, w[4] | phase);
          st_rlx1(dst + 128 + lane, w[0] | phase);
          TR(3);
        }
        {
          const int mt = warp & 1;
          const int nt0 = (warp >> 1) ? 3 : 0, nn = (warp >> 1) ? 2 : 3;
          float sc[3][4];
#pragma unroll
          for (int j = 0; j < 3; j++) { sc[j][0] = sc[j][1] = sc[j][2] = sc[j][3] = 0.f; }
          const int fr = (lane & 7) + ((lane >> 4) & 1) * 8;
          const uint32_t qa = qkb + fr * 64 + (((2 * mt + ((lane >> 3) & 1)) ^ ((fr >> 1) & 3)) << 4);
#pragma unroll
          for (int kb = 0; kb < 3; kb++) {
            uint32_t a[2][4];
            ldsm_x4_t(a[0][0], a[0][1], a[0][2], a[0][3], qa + kb * 2048);
            ldsm_x4_t(a[1][0], a[1][1], a[1][2], a[1][3], qa + kb * 2048 + 1024);
#pragma unroll
            for (int j = 0; j < 3; j++) {
              if (j < nn) {
                int nt = nt0 + j;
                uint32_t ka = (nt == 0) ? (qm_a + 1536 + kb * 512) : (qkb + (96 + lane) * 64 + (((nt - 1) ^ swz) << 4) + kb * 2048);
                uint32_t b0, b1, b2, b3;
                ldsm_x4_t(b0, b1, b2, b3, ka);
                mma_bf16(sc[j], a[0][0], a[0][1], a[0][2], a[0][3], b0, b1);
                mma_bf16(sc[j], a[1][0], a[1][1], a[1][2], a[1][3], b2, b3);
              }
            }
          }
          if (rank == 1) {
#pragma unroll
            for (int j = 0; j < 3; j++) if (j < nn) sts4f(sb + QK_SCX + 5120 + (mt * 5 + nt0 + j) * 512 + lane * 16, sc[j][0], sc[j][1], sc[j][2], sc[j][3]);
            __syncwarp();
            if (lane == 0) { if (warp == 0) mbar_arrive_tx(barX, 5120); else mbar_arrive(barX); }
          } else {
#pragma unroll
            for (int j = 0; j < 3; j++) if (j < nn) st_async4(scx_r + (mt * 5 + nt0 + j) * 512, sc[j][0], sc[j][1], sc[j][2], sc[j][3], barX1);
          }
        }
        bar_arrive(3, 512);
        TR(4);
        if (rank == 1) {
          mbar_wait(barX, t & 1);
          float s[5][2];
          const int qrow = 8 * (g >> 1) + 2 * warp + (g & 1);
#pragma unroll
          for (int j = 0; j < 5; j++) {
            float2 u = lds2f(sb + QK_SCX + ((warp >> 1) * 5 + j) * 512 + lane * 16 + (warp & 1) * 8);
            float2 v = lds2f(sb + QK_SCX + 5120 + ((warp >> 1) * 5 + j) * 512 + lane * 16 + (warp & 1) * 8);
            s[j][0] = bf16r(bf16r(u.x + v.x) * SCALE);
            s[j][1] = bf16r(bf16r(u.y + v.y) * SCALE);
            if (j > 0) {
              int k0 = 8 * qi + 2 * (j - 1);
              if (k0 > qrow) s[j][0] = -1e9f;
              if (k0 + 1 > qrow) s[j][1] = -1e9f;
            }
          }
          uint32_t w[5];
          softmax_row(s, w);
          uint32_t* dst = g_p + ((size_t)((t & 3) * 5 + 1 + warp) * 32 + h) * 160;
          st_rlx4(dst + lane * 4, w[1] | phase, w[2] | phase, w[3] | phase, w[4] | phase);
          st_rlx1(dst + 128 + lane, w[0] | phase);
        }
        if (reducer) {
          if (wt == 0 && !bload) {
            int guard = 0;
            while (ld_acq1(&g_cntB[t]) != 128u) { if (++guard > SPIN_LIMIT) { g_err = 8; break; } }
            fence_async_all();
            mbar_arrive_tx(barB, 32768);
            bulk_g2s(sb + QK_BSL, g_B + ((size_t)(t & 3) * 40 + qidx) * 8192, 32768, barB);
          }
          __syncwarp();
          const uint32_t* gp = g_p + ((size_t)((t & 3) * 5) * 32 + warp * 8) * 160;
          const uint32_t* gz = g_z + (((size_t)(t & 3) * 40 + qidx) * 32 + warp * 8) * 64;
          {
            const uint32_t* sp = (lane & 8) ? gz + (lane & 7) * 64 + 63 : gp + (lane & 7) * 160 + 159;
            int guard = 0;
            while (true) {
              uint32_t w = ld_rlx1(sp);
              bool ok = (lane & 8) ? (w != CANARY) : (((w ^ phase) & 0x80008000u) == 0);
              if (__all_sync(0xffffffffu, ok)) break;
              if (++guard > SPIN_LIMIT) { g_err = 7; break; }
            }
          }
          TR(5);
          const uint32_t pl = sb + QK_PL + warp * 5120;
          float acc[8];
          bool first = true;
          int guard = 0;
          while (true) {
#pragma unroll
            for (int i = 0; i < 10; i++) cp_async16(pl + (lane + 32 * i) * 16, gp + (lane + 32 * i) * 4);
            cp_async_commit();
            uint2 z[8];
#pragma unroll
            for (int hh = 0; hh < 8; hh++) z[hh] = ld_rlx2(gz + hh * 64 + lane * 2);
            if (first) { mbar_wait(barB, t & 1); bar_sync(4, 512); first = false; }
            cp_async_wait0();
            __syncwarp();
            uint32_t bad = 0, zbad = 0;
#pragma unroll
            for (int i = 0; i < 8; i++) acc[i] = 0.f;
#pragma unroll
            for (int hp = 0; hp < 4; hp++) {
              uint32_t pm0 = lds1(pl + (2 * hp) * 640 + 512 + lane * 4), pm1 = lds1(pl + (2 * hp + 1) * 640 + 512 + lane * 4);
              bad |= (pm0 ^ phase) | (pm1 ^ phase);
              zbad |= (z[2 * hp].x == CANARY) | (z[2 * hp].y == CANARY) | (z[2 * hp + 1].x == CANARY) | (z[2 * hp + 1].y == CANARY);
              mma_bf16(acc + (hp & 1) * 4, z[2 * hp].x, z[2 * hp].y, z[2 * hp + 1].x, z[2 * hp + 1].y, pm0 & 0x7fff7fffu, pm1 & 0x7fff7fffu);
#pragma unroll
              for (int u = 0; u < 2; u++) {
                const int hh = 2 * hp + u;
                uint4 px = lds4(pl + hh * 640 + lane * 16);
                uint4 B0 = lds4(sb + QK_BSL + (warp * 8 + hh) * 1024 + lane * 16);
                uint4 B1 = lds4(sb + QK_BSL + (warp * 8 + hh) * 1024 + 512 + lane * 16);
                bad |= (px.x ^ phase) | (px.y ^ phase) | (px.z ^ phase) | (px.w ^ phase);
                mma_bf16(acc, B0.x, B0.y, B0.z, B0.w, px.x & 0x7fff7fffu, px.y & 0x7fff7fffu);
                mma_bf16(acc + 4, B1.x, B1.y, B1.z, B1.w, px.z & 0x7fff7fffu, px.w & 0x7fff7fffu);
              }
            }
            if (!__any_sync(0xffffffffu, ((bad & 0x80008000u) | zbad) != 0)) break;
            if (++guard > SPIN_LIMIT) { g_err = 4; break; }
          }
          const uint32_t ra = sb + QK_RED + warp * 640 + (2 * qi) * 80 + g * 4;
          sts1f(ra, acc[0] + acc[4]); sts1f(ra + 80, acc[1] + acc[5]); sts1f(ra + 32, acc[2] + acc[6]); sts1f(ra + 112, acc[3] + acc[7]);
          bar_arrive(5, 512);
          bar_sync(6, 128);
          if (wt < 64) {
            const int row = wt >> 3, cp = wt & 7;
            const uint32_t rr = sb + QK_RED + row * 80 + cp * 8;
            float2 a0 = lds2f(rr), a1 = lds2f(rr + 640), a2 = lds2f(rr + 1280), a3 = lds2f(rr + 1920);
            uint32_t w = pack_bf16((a0.x + a1.x) + (a2.x + a3.x), (a0.y + a1.y) + (a2.y + a3.y));
            st_rlx1(g_mem + ((t + 1) & 3) * 2560 + row * 320 + qidx * 8 + cp, w);
            st_rlx1(g_mem + ((t + 3) & 3) * 2560 + row * 320 + qidx * 8 + cp, CANARY);
          }
          TR(6);
          bar_sync(6, 128);
        }
      }
    }
  } else {
    const uint32_t barV = sb + VO_BAR, barPC = barV + 8, xnF = barV + 16, xnE = barV + 24, barPB = barV + 32, barVX = barV + 40;
    if (tid == 0) {
      mbar_init(barV, 8); mbar_init(barPC, 1); mbar_init(xnF, 1); mbar_init(xnE, 16); mbar_init(barPB, 1); mbar_init(barVX, 5);
      asm volatile("fence.mbarrier_init.release.cluster;" ::: "memory");
    }
    const bf16* wv = P.Wv + h * DH_;
    const bf16* wo = P.Wo + (size_t)h * DH_ * 640 + 320 * rank;
    const int f0 = rank * 128;
    load_tile(sb + 98304, 640, wv + f0, wv + f0 + 32, 6144, tid);
    load_tile(sb, 320, wv + (size_t)(320 * rank) * 6144 + 64, wv + (size_t)(320 * rank) * 6144 + 96, 6144, tid);
    load_tile(sb + 40960, 192, wo, wo + 32, 640, tid);
    cp_async_commit();
    cluster_sync();
    const uint32_t baddr = sb + VO_MEM + (lane & 7) * 1296 + (lane >> 3) * 16;
    const uint64_t xdesc = mkdesc(sb + VO_XN, 16, 1024, 1);
    const uint64_t vdesc = mkdesc(sb + VO_VX, 512, 512, 2);
    const uint32_t xnE_r = mapa(xnE, rank ^ 1);
    const uint32_t vm_a = sb + VO_VM + lane * 16;
    auto load_res = [&]() {
#pragma unroll
      for (int T = 0; T < 4; T++) load_tile(sb + VO_WO + T * 24576, 192, wo + 64 * (T + 1), wo + 64 * (T + 1) + 32, 640, tid);
      cp_async_commit();
    };
    auto z_smem = [&](int T, int t) {
      float z[8];
#pragma unroll
      for (int i = 0; i < 8; i++) z[i] = 0.f;
#pragma unroll
      for (int kb = 0; kb < 6; kb++) {
        uint32_t b0, b1, b2, b3, a0, a1, a2, a3, c0, c1, c2, c3;
        ldsm_x4_t(b0, b1, b2, b3, vm_a + (t & 3) * 3072 + kb * 512);
        ldsm_x4_t(a0, a1, a2, a3, sb + VO_WO + (T - 1) * 24576 + a_off + (2 * kb) * 2048);
        ldsm_x4_t(c0, c1, c2, c3, sb + VO_WO + (T - 1) * 24576 + a_off + (2 * kb + 1) * 2048);
        mma_bf16(z, a0, a1, a2, a3, b0, b1);
        mma_bf16(z + 4, c0, c1, c2, c3, b2, b3);
      }
      const size_t o = ((size_t)(20 * rank + 4 * T + warp) * 32 + h) * 64 + lane * 2;
      st_rlx2(g_z + (size_t)(t & 3) * 81920 + o, pack_bf16(z[0] + z[4], z[1] + z[5]), pack_bf16(z[2] + z[6], z[3] + z[7]));
      st_rlx2(g_z + (size_t)((t + 3) & 3) * 81920 + o, CANARY, CANARY);
    };
    auto store_B = [&](const float* d, int T, int seg) {
      uint32_t* dst = g_B + (((size_t)(seg & 3) * 40 + 20 * rank + 4 * T + warp) * 32 + h) * 256 + lane * 4;
      *reinterpret_cast<uint4*>(dst) = make_uint4(pack_bf16(d[0], d[1]), pack_bf16(d[2], d[3]), pack_bf16(d[4], d[5]), pack_bf16(d[6], d[7]));
      *reinterpret_cast<uint4*>(dst + 128) = make_uint4(pack_bf16(d[8], d[9]), pack_bf16(d[10], d[11]), pack_bf16(d[12], d[13]), pack_bf16(d[14], d[15]));
    };
    if (wg == 0) {
      asm volatile("setmaxnreg.inc.sync.aligned.u32 200;");
      uint32_t W[40][4];
      cp_async_wait0();
      __syncthreads();
#pragma unroll
      for (int ks = 0; ks < 40; ks++) ldsm_x4_t(W[ks][0], W[ks][1], W[ks][2], W[ks][3], sb + 98304 + a_off + ks * 2048);
      __syncthreads();
      load_res();
      cluster_sync();
      if (tid == 0) {
        mbar_arrive_tx(xnF, 40960);
        bulk_g2s_mc(sb + VO_XN + rank * 20480, reinterpret_cast<const uint8_t*>(g_xnT) + rank * 20480, 20480, xnF, 3);
      }
      cp_async_wait0();
      fence_async_smem();
      __syncthreads();
      const int feat = f0 + warp * 16 + g;
      const uint32_t barV_r = mapa(barV, rank ^ 1);
      const uint32_t vm_r = mapa(sb + VO_VM + feat * 16 + qi * 4, rank ^ 1);
      for (int t = -2; t < NSEG; t++) {
        float d[16];
        if (t >= 0) {
          bar_sync(1, 512);
          TR(8);
#pragma unroll
          for (int i = 0; i < 16; i++) d[i] = 0.f;
#pragma unroll
          for (int kp = 0; kp < 20; kp++) {
            uint32_t b0, b1, b2, b3;
            ldsm_x4(b0, b1, b2, b3, baddr + kp * 64);
            mma_bf16(d + ((2 * kp) & 3) * 4, W[2 * kp][0], W[2 * kp][1], W[2 * kp][2], W[2 * kp][3], b0, b1);
            mma_bf16(d + ((2 * kp + 1) & 3) * 4, W[2 * kp + 1][0], W[2 * kp + 1][1], W[2 * kp + 1][2], W[2 * kp + 1][3], b2, b3);
          }
          uint32_t w0 = pack_bf16((d[0] + d[4]) + (d[8] + d[12]), (d[1] + d[5]) + (d[9] + d[13]));
          uint32_t w1 = pack_bf16((d[2] + d[6]) + (d[10] + d[14]), (d[3] + d[7]) + (d[11] + d[15]));
          st_async1(vm_r + (t & 3) * 3072, w0, barV_r);
          st_async1(vm_r + (t & 3) * 3072 + 128, w1, barV_r);
          sts1(sb + VO_VM + (t & 3) * 3072 + feat * 16 + qi * 4, w0);
          sts1(sb + VO_VM + (t & 3) * 3072 + feat * 16 + 128 + qi * 4, w1);
          __syncwarp();
          if (lane == 0) { if (warp == 0) mbar_arrive_tx(barV, 1024); else mbar_arrive(barV); }
          bar_arrive(2, 384);
          TR(9);
          mbar_wait(barV, t & 1);
          TR(10);
          z_smem(1, t);
          TR(11);
          bar_sync(3, 512);
        }
        if (t + 2 < NSEG) {
          mbar_wait(xnF, t & 1);
#pragma unroll
          for (int i = 0; i < 16; i++) d[i] = 0.f;
          WG_FENCE();
#pragma unroll
          for (int ks = 0; ks < 40; ks++) rs32<0>(d, W[ks], xdesc + xoff(ks));
          WG_COMMIT();
          WG_WAIT0();
          if (lane == 0) { mbar_arrive(xnE); mbar_arrive_remote(xnE_r); }
          const uint32_t vb = sb + VO_VX + ((t + 2) & 3) * 12288;
          const uint32_t qa = vb + feat * 64 + ((qi ^ ((feat >> 1) & 3)) << 4);
          sts4(qa, pack_bf16(d[0], d[1]), pack_bf16(d[4], d[5]), pack_bf16(d[8], d[9]), pack_bf16(d[12], d[13]));
          sts4(qa + 512, pack_bf16(d[2], d[3]), pack_bf16(d[6], d[7]), pack_bf16(d[10], d[11]), pack_bf16(d[14], d[15]));
          fence_async_smem();
          bar_sync(7, 128);
          TR(12);
          if (wt == 0) {
            bulk_s2s(mapa(vb + f0 * 64, rank ^ 1), vb + f0 * 64, 4096, mapa(barVX, rank ^ 1));
            mbar_arrive_tx(barVX, 4096);
            if (t + 3 < NSEG) {
              mbar_wait(xnE, t & 1);
              mbar_arrive_tx(xnF, 40960);
              bulk_g2s_mc(sb + VO_XN + rank * 20480, reinterpret_cast<const uint8_t*>(g_xnT) + (size_t)(t + 3) * 40960 + rank * 20480, 20480, xnF, 3);
            }
          }
          __syncwarp();
        }
      }
    } else if (wg == 1) {
      asm volatile("setmaxnreg.inc.sync.aligned.u32 200;");
      uint32_t W[20][4], WO[12][4];
      cp_async_wait0();
      __syncthreads();
#pragma unroll
      for (int ks = 0; ks < 20; ks++) ldsm_x4_t(W[ks][0], W[ks][1], W[ks][2], W[ks][3], sb + a_off + ks * 2048);
#pragma unroll
      for (int ks = 0; ks < 12; ks++) ldsm_x4_t(WO[ks][0], WO[ks][1], WO[ks][2], WO[ks][3], sb + 40960 + a_off + ks * 2048);
      __syncthreads();
      load_res();
      cluster_sync();
      cp_async_wait0();
      fence_async_smem();
      __syncthreads();
      const int feat = 64 + warp * 16 + g;
      const uint32_t pc_r = mapa(sb + VO_PC + wt * 16, rank ^ 1), barPC_r = mapa(barPC, rank ^ 1);
      const uint32_t pb_r = mapa(sb + VO_PB + wt * 16, rank ^ 1), barPB_r = mapa(barPB, rank ^ 1);
      const uint64_t xdesc1 = xdesc + (uint64_t)(rank * (20480 >> 4));
      for (int t = -2; t < NSEG; t++) {
        float d[16], e[16];
        if (t >= 0) {
          if (wt == 0) mbar_arrive_tx(barPC, 2048);
          bar_sync(1, 512);
#pragma unroll
          for (int i = 0; i < 16; i++) d[i] = 0.f;
#pragma unroll
          for (int kp = 0; kp < 10; kp++) {
            uint32_t b0, b1, b2, b3;
            ldsm_x4(b0, b1, b2, b3, baddr + rank * 640 + kp * 64);
            mma_bf16(d + ((2 * kp) & 3) * 4, W[2 * kp][0], W[2 * kp][1], W[2 * kp][2], W[2 * kp][3], b0, b1);
            mma_bf16(d + ((2 * kp + 1) & 3) * 4, W[2 * kp + 1][0], W[2 * kp + 1][1], W[2 * kp + 1][2], W[2 * kp + 1][3], b2, b3);
          }
          float r0 = (d[0] + d[4]) + (d[8] + d[12]), r1 = (d[1] + d[5]) + (d[9] + d[13]);
          float r2 = (d[2] + d[6]) + (d[10] + d[14]), r3 = (d[3] + d[7]) + (d[11] + d[15]);
          st_async4(pc_r, r0, r1, r2, r3, barPC_r);
          bar_arrive(2, 384);
          mbar_wait(barPC, t & 1);
          float4 o = lds4f(sb + VO_PC + wt * 16);
          sts1(sb + VO_VM + (t & 3) * 3072 + feat * 16 + qi * 4, pack_bf16(r0 + o.x, r1 + o.y));
          sts1(sb + VO_VM + (t & 3) * 3072 + feat * 16 + 128 + qi * 4, pack_bf16(r2 + o.z, r3 + o.w));
          __syncwarp();
          if (lane == 0) mbar_arrive(barV);
          mbar_wait(barV, t & 1);
          {
#pragma unroll
            for (int i = 0; i < 8; i++) d[i] = 0.f;
#pragma unroll
            for (int kb = 0; kb < 6; kb++) {
              uint32_t b0, b1, b2, b3;
              ldsm_x4_t(b0, b1, b2, b3, vm_a + (t & 3) * 3072 + kb * 512);
              mma_bf16(d, WO[2 * kb][0], WO[2 * kb][1], WO[2 * kb][2], WO[2 * kb][3], b0, b1);
              mma_bf16(d + 4, WO[2 * kb + 1][0], WO[2 * kb + 1][1], WO[2 * kb + 1][2], WO[2 * kb + 1][3], b2, b3);
            }
            const size_t o2 = ((size_t)(20 * rank + warp) * 32 + h) * 64 + lane * 2;
            st_rlx2(g_z + (size_t)(t & 3) * 81920 + o2, pack_bf16(d[0] + d[4], d[1] + d[5]), pack_bf16(d[2] + d[6], d[3] + d[7]));
            st_rlx2(g_z + (size_t)((t + 3) & 3) * 81920 + o2, CANARY, CANARY);
          }
          z_smem(2, t);
        }
        if (t + 1 >= 0 && t + 1 < NSEG) { mbar_wait(barVX, (t + 1) & 1); fence_async_smem(); }
        if (t >= 0) bar_sync(3, 512);
        if (t + 2 < NSEG) {
          if (wt == 0) mbar_arrive_tx(barPB, 8192);
          mbar_wait(xnF, t & 1);
#pragma unroll
          for (int i = 0; i < 16; i++) d[i] = 0.f;
          WG_FENCE();
#pragma unroll
          for (int ks = 0; ks < 20; ks++) rs32<0>(d, W[ks], xdesc1 + xoff(ks));
          WG_COMMIT();
          WG_WAIT0();
          if (lane == 0) { mbar_arrive(xnE); mbar_arrive_remote(xnE_r); }
#pragma unroll
          for (int i = 0; i < 4; i++) st_async4(pb_r + i * 2048, d[4 * i], d[4 * i + 1], d[4 * i + 2], d[4 * i + 3], barPB_r);
        }
        if (t + 1 >= 0 && t + 1 < NSEG) {
#pragma unroll
          for (int i = 0; i < 16; i++) e[i] = 0.f;
          const uint64_t vd = vdesc + (uint64_t)(((t + 1) & 3) * (12288 >> 4));
          WG_FENCE();
#pragma unroll
          for (int ks = 0; ks < 12; ks++) rs32<1>(e, WO[ks], vd + ks * 64);
          WG_COMMIT();
          WG_WAIT0();
          store_B(e, 0, t + 1);
          bar_sync(8, 128);
          if (wt == 0) { __threadfence(); atomicAdd(&g_cntB[t + 1], 1u); }
        }
        if (t + 2 < NSEG) {
          mbar_wait(barPB, t & 1);
#pragma unroll
          for (int i = 0; i < 4; i++) {
            float4 o = lds4f(sb + VO_PB + i * 2048 + wt * 16);
            d[4 * i] += o.x; d[4 * i + 1] += o.y; d[4 * i + 2] += o.z; d[4 * i + 3] += o.w;
          }
          const uint32_t qa = sb + VO_VX + ((t + 2) & 3) * 12288 + feat * 64 + ((qi ^ ((feat >> 1) & 3)) << 4);
          sts4(qa, pack_bf16(d[0], d[1]), pack_bf16(d[4], d[5]), pack_bf16(d[8], d[9]), pack_bf16(d[12], d[13]));
          sts4(qa + 512, pack_bf16(d[2], d[3]), pack_bf16(d[6], d[7]), pack_bf16(d[10], d[11]), pack_bf16(d[14], d[15]));
          fence_async_smem();
          __syncwarp();
          if (lane == 0) mbar_arrive(barVX);
          TR(13);
        }
      }
    } else if (wg == 2) {
      asm volatile("setmaxnreg.dec.sync.aligned.u32 56;");
      cp_async_wait0();
      __syncthreads();
      __syncthreads();
      load_res();
      cluster_sync();
      cp_async_wait0();
      fence_async_smem();
      __syncthreads();
      const uint64_t wdesc = mkdesc(sb + VO_WO, 1024, 1024, 1);
      for (int t = -1; t < NSEG; t++) {
        if (t >= 0) {
          bar_sync(1, 512);
          mbar_wait(barV, t & 1);
          z_smem(3, t);
          z_smem(4, t);
        }
        if (t + 1 < NSEG) { mbar_wait(barVX, (t + 1) & 1); fence_async_smem(); }
        if (t >= 0) bar_sync(3, 512);
        if (t + 1 < NSEG) {
          const uint64_t vd = vdesc + (uint64_t)(((t + 1) & 3) * (12288 >> 4));
#pragma unroll
          for (int T2 = 0; T2 < 2; T2++) {
            float e[16], f[16];
#pragma unroll
            for (int i = 0; i < 16; i++) { e[i] = 0.f; f[i] = 0.f; }
            WG_FENCE();
#pragma unroll
            for (int ks = 0; ks < 12; ks++) ss32<1, 1>(e, wdesc + (2 * T2) * 1536 + ks * 128, vd + ks * 64);
#pragma unroll
            for (int ks = 0; ks < 12; ks++) ss32<1, 1>(f, wdesc + (2 * T2 + 1) * 1536 + ks * 128, vd + ks * 64);
            WG_COMMIT();
            WG_WAIT0();
            store_B(e, 2 * T2 + 1, t + 1);
            store_B(f, 2 * T2 + 2, t + 1);
          }
          bar_sync(9, 128);
          if (wt == 0) { __threadfence(); atomicAdd(&g_cntB[t + 1], 1u); }
          TR(14);
        }
      }
    } else {
      asm volatile("setmaxnreg.dec.sync.aligned.u32 56;");
      cp_async_wait0();
      __syncthreads();
      __syncthreads();
      load_res();
      cluster_sync();
      cp_async_wait0();
      fence_async_smem();
      __syncthreads();
      const int mt = warp & 1, nb = (warp >> 1) * 6;
      uint4 px[2]; uint32_t pm[2];
      auto load_P = [&](int tau) {
        const uint32_t phase = ((((tau >> 2) & 1) ^ 1) != 0) ? 0x80008000u : 0u;
        const uint32_t* src = g_p + ((size_t)((tau & 3) * 5 + 1 + 2 * mt) * 32 + h) * 160;
        int guard = 0;
        while (true) {
          uint32_t bad = 0;
#pragma unroll
          for (int j = 0; j < 2; j++) {
            px[j] = ld_rlx4(src + j * 5120 + lane * 4);
            pm[j] = ld_rlx1(src + j * 5120 + 128 + lane);
          }
#pragma unroll
          for (int j = 0; j < 2; j++) bad |= (px[j].x ^ phase) | (px[j].y ^ phase) | (px[j].z ^ phase) | (px[j].w ^ phase) | (pm[j] ^ phase);
          if (!__any_sync(0xffffffffu, (bad & 0x80008000u) != 0)) break;
          if (++guard > SPIN_LIMIT) { g_err = 3; break; }
          __nanosleep(100);
        }
#pragma unroll
        for (int j = 0; j < 2; j++) { px[j].x &= 0x7fff7fffu; px[j].y &= 0x7fff7fffu; px[j].z &= 0x7fff7fffu; px[j].w &= 0x7fff7fffu; pm[j] &= 0x7fff7fffu; }
      };
      auto do_ox = [&](int tau) {
        const int fb = 96 * rank + nb * 8;
        const int fl = fb + (lane & 7);
        const uint32_t vxa = sb + VO_VX + (tau & 3) * 12288 + fl * 64;
        uint32_t bm[8];
        ldsm_x4(bm[0], bm[1], bm[2], bm[3], sb + VO_VM + (tau & 3) * 3072 + (fb + lane) * 16);
        ldsm_x4(bm[4], bm[5], bm[6], bm[7], sb + VO_VM + (tau & 3) * 3072 + (fb + 32 + (lane & 15)) * 16);
        const int r0 = 8 * (g >> 1) + 4 * mt + (g & 1);
        bf16* dst = g_ox + (size_t)(tau * 32 + r0) * 6144 + h * DH_ + fb + 2 * qi;
#pragma unroll
        for (int n = 0; n < 6; n++) {
          uint32_t b0, b1, b2, b3;
          ldsm_x4(b0, b1, b2, b3, vxa + n * 512 + (((lane >> 3) ^ ((fl >> 1) & 3)) << 4));
          float o[4] = {0.f, 0.f, 0.f, 0.f};
          mma_bf16_k8(o, pm[0], pm[1], bm[n]);
          mma_bf16(o, px[0].x, px[1].x, px[0].y, px[1].y, b0, b1);
          mma_bf16(o, px[0].z, px[1].z, px[0].w, px[1].w, b2, b3);
          *reinterpret_cast<uint32_t*>(dst + n * 8) = pack_bf16(o[0], o[1]);
          *reinterpret_cast<uint32_t*>(dst + (size_t)2 * 6144 + n * 8) = pack_bf16(o[2], o[3]);
        }
      };
      for (int t = 0; t < NSEG; t++) {
        poll_mem(t & 3, sb + VO_MEM, warp, lane);
        bar_sync(1, 512);
        TR(0);
        bar_sync(2, 384);
        TR(1);
        if (t > 0) do_ox(t - 1);
        TR(2);
        bar_sync(3, 512);
        TR(3);
        load_P(t);
        TR(4);
      }
      do_ox(NSEG - 1);
    }
  }
  cluster_sync();
}

extern "C" void kernel_launch(void* const* d_in, const int* in_sizes, int n_in, void* d_out, int out_size) {
  const bf16* x = (const bf16*)d_in[0];
  const bf16* mem0 = (const bf16*)d_in[1];
  const bf16* Wq = (const bf16*)d_in[2];
  const bf16* Wk = (const bf16*)d_in[3];
  const bf16* Wv = (const bf16*)d_in[4];
  const bf16* Wo = (const bf16*)d_in[5];
  const bf16* w1 = (const bf16*)d_in[8];
  const bf16* b1 = (const bf16*)d_in[9];
  const bf16* w2 = (const bf16*)d_in[10];
  const bf16* b2 = (const bf16*)d_in[11];
  bf16* out = (bf16*)d_out;
  cudaStream_t st = cudaStreamPerThread;

  static bool init = false;
  static bf16 *p_y, *p_hmid, *p_gate, *p_ox;
  if (!init) {
    cudaFuncSetAttribute(chain_kernel, cudaFuncAttributeMaxDynamicSharedMemorySize, CHAIN_SMEM);
    cudaGetSymbolAddress((void**)&p_y, g_y);
    cudaGetSymbolAddress((void**)&p_hmid, g_hmid);
    cudaGetSymbolAddress((void**)&p_gate, g_gate);
    cudaGetSymbolAddress((void**)&p_ox, g_ox);
    init = true;
  }
  ln_kernel<<<256, 256, 0, st>>>(x, mem0);
  gemm_kernel<1><<<dim3(12, 16, 1), 256, 0, st>>>(p_y, 640, 0, w1, 1536, 0, p_hmid, 1536, 0, b1, 640);
  gemm_kernel<2><<<dim3(5, 16, 1), 256, 0, st>>>(p_hmid, 1536, 0, w2, 640, 0, p_gate, 640, 0, b2, 1536);
  ChainParams P{Wq, Wk, Wv, Wo};
  chain_kernel<<<128, 512, CHAIN_SMEM, st>>>(P);
  gemm_kernel<3><<<dim3(5, 16, 1), 256, 0, st>>>(p_ox, 6144, 0, Wo, 640, 0, out, 640, 0, nullptr, 6144, x, p_gate);
}
```

```cpp
#include <cuda_runtime.h>
#include <cuda.h>
#include <cuda_bf16.h>
#include <stdint.h>

typedef __nv_bfloat16 bf16;

constexpr int S_ = 2048, D_ = 640, H_ = 32, DH_ = 192, NSEG = 64, F_ = 1536;
constexpr int SPIN_LIMIT = 1 << 20;
constexpr uint32_t CANARY = 0xFFFFFFFFu;

__device__ uint4 g_xnT[64 * 2560];
__device__ uint4 g_y4[128 * 40 * 32];
__device__ uint4 g_h4[128 * 96 * 32];
__device__ uint4 g_ox4[128 * 384 * 32];
__device__ uint4 g_gt4[32 * 20 * 256];
__device__ uint4 g_part[32 * 16 * 5 * 256];
__device__ uint32_t g_flag[32];
__device__ uint4 g_B4[2 * 32 * 2 * 20 * 64];
#define NCP 2
__device__ __align__(4096) uint32_t g_mem[NCP * 4 * 2560];
__device__ __align__(4096) uint32_t g_pt[4 * 64 * 1280];
__device__ __align__(4096) uint32_t g_zq[4 * 64 * 1280];
__device__ __align__(4096) uint32_t g_pm[4 * 2 * 32 * 32];
__device__ unsigned long long g_cnt;
__device__ uint4 g_p4[4 * 4 * 32 * 40];
__device__ int g_err;
#define g_B ((uint32_t*)g_B4)
#define g_p ((uint32_t*)g_p4)
#define TRW(slot, w) do {} while (0)
#define TR(slot) do {} while (0)

#define TLM(k) do {} while (0)
#define DBG(k) do {} while (0)
__device__ __forceinline__ uint32_t smem_u32(const void* p) { return (uint32_t)__cvta_generic_to_shared(p); }
__device__ __forceinline__ void ldsm_x4(uint32_t& r0, uint32_t& r1, uint32_t& r2, uint32_t& r3, uint32_t addr) {
  asm volatile("ldmatrix.sync.aligned.m8n8.x4.shared.b16 {%0,%1,%2,%3}, [%4];" : "=r"(r0), "=r"(r1), "=r"(r2), "=r"(r3) : "r"(addr));
}
__device__ __forceinline__ void ldsm_x4_t(uint32_t& r0, uint32_t& r1, uint32_t& r2, uint32_t& r3, uint32_t addr) {
  asm volatile("ldmatrix.sync.aligned.m8n8.x4.trans.shared.b16 {%0,%1,%2,%3}, [%4];" : "=r"(r0), "=r"(r1), "=r"(r2), "=r"(r3) : "r"(addr));
}
__device__ __forceinline__ void mma_bf16(float* c, uint32_t a0, uint32_t a1, uint32_t a2, uint32_t a3, uint32_t b0, uint32_t b1) {
  asm("mma.sync.aligned.m16n8k16.row.col.f32.bf16.bf16.f32 {%0,%1,%2,%3}, {%4,%5,%6,%7}, {%8,%9}, {%0,%1,%2,%3};"
      : "+f"(c[0]), "+f"(c[1]), "+f"(c[2]), "+f"(c[3]) : "r"(a0), "r"(a1), "r"(a2), "r"(a3), "r"(b0), "r"(b1));
}
__device__ __forceinline__ void mma_bf16_k8(float* c, uint32_t a0, uint32_t a1, uint32_t b0) {
  asm("mma.sync.aligned.m16n8k8.row.col.f32.bf16.bf16.f32 {%0,%1,%2,%3}, {%4,%5}, {%6}, {%0,%1,%2,%3};"
      : "+f"(c[0]), "+f"(c[1]), "+f"(c[2]), "+f"(c[3]) : "r"(a0), "r"(a1), "r"(b0));
}
__device__ __forceinline__ void cp_async16(uint32_t dst, const void* src) {
  asm volatile("cp.async.cg.shared.global [%0], [%1], 16;" :: "r"(dst), "l"(src) : "memory");
}
__device__ __forceinline__ void cp_async_commit() { asm volatile("cp.async.commit_group;" ::: "memory"); }
__device__ __forceinline__ void cp_async_wait0() { asm volatile("cp.async.wait_group 0;" ::: "memory"); }
__device__ __forceinline__ void bar_sync(int id, int n) { asm volatile("bar.sync %0, %1;" :: "r"(id), "r"(n) : "memory"); }
__device__ __forceinline__ void bar_arrive(int id, int n) { asm volatile("bar.arrive %0, %1;" :: "r"(id), "r"(n) : "memory"); }
__device__ __forceinline__ uint4 ld_rlx4(const uint32_t* p) {
  uint4 v;
  asm volatile("ld.relaxed.gpu.global.v4.u32 {%0,%1,%2,%3}, [%4];" : "=r"(v.x), "=r"(v.y), "=r"(v.z), "=r"(v.w) : "l"(p) : "memory");
  return v;
}
__device__ __forceinline__ uint2 ld_rlx2(const uint32_t* p) {
  uint2 v;
  asm volatile("ld.relaxed.gpu.global.v2.u32 {%0,%1}, [%2];" : "=r"(v.x), "=r"(v.y) : "l"(p) : "memory");
  return v;
}
__device__ __forceinline__ uint32_t ld_rlx1(const uint32_t* p) {
  uint32_t v;
  asm volatile("ld.relaxed.gpu.global.u32 %0, [%1];" : "=r"(v) : "l"(p) : "memory");
  return v;
}
__device__ __forceinline__ uint32_t ld_acq1(const uint32_t* p) {
  uint32_t v;
  asm volatile("ld.acquire.gpu.global.u32 %0, [%1];" : "=r"(v) : "l"(p) : "memory");
  return v;
}
__device__ __forceinline__ void st_rlx4(uint32_t* p, uint32_t a, uint32_t b, uint32_t c, uint32_t d) {
  asm volatile("st.relaxed.gpu.global.v4.u32 [%0], {%1,%2,%3,%4};" :: "l"(p), "r"(a), "r"(b), "r"(c), "r"(d) : "memory");
}
__device__ __forceinline__ void st_rlx2(uint32_t* p, uint32_t a, uint32_t b) {
  asm volatile("st.relaxed.gpu.global.v2.u32 [%0], {%1,%2};" :: "l"(p), "r"(a), "r"(b) : "memory");
}
__device__ __forceinline__ void st_rlx1(uint32_t* p, uint32_t a) {
  asm volatile("st.relaxed.gpu.global.u32 [%0], %1;" :: "l"(p), "r"(a) : "memory");
}
__device__ __forceinline__ void stg4(void* p, uint32_t a, uint32_t b, uint32_t c, uint32_t d) {
  asm volatile("st.global.v4.u32 [%0], {%1,%2,%3,%4};" :: "l"(p), "r"(a), "r"(b), "r"(c), "r"(d) : "memory");
}
__device__ __forceinline__ void stg1(void* p, uint32_t a) { asm volatile("st.global.u32 [%0], %1;" :: "l"(p), "r"(a) : "memory"); }
__device__ __forceinline__ void sts1(uint32_t addr, uint32_t a) { asm volatile("st.shared.u32 [%0], %1;" :: "r"(addr), "r"(a) : "memory"); }
__device__ __forceinline__ void sts1f(uint32_t addr, float a) { asm volatile("st.shared.f32 [%0], %1;" :: "r"(addr), "f"(a) : "memory"); }
__device__ __forceinline__ void sts2f(uint32_t addr, float a, float b) { asm volatile("st.shared.v2.f32 [%0], {%1,%2};" :: "r"(addr), "f"(a), "f"(b) : "memory"); }
__device__ __forceinline__ void sts4(uint32_t addr, uint32_t a, uint32_t b, uint32_t c, uint32_t d) {
  asm volatile("st.shared.v4.u32 [%0], {%1,%2,%3,%4};" :: "r"(addr), "r"(a), "r"(b), "r"(c), "r"(d) : "memory");
}
__device__ __forceinline__ void sts4f(uint32_t addr, float a, float b, float c, float d) {
  asm volatile("st.shared.v4.f32 [%0], {%1,%2,%3,%4};" :: "r"(addr), "f"(a), "f"(b), "f"(c), "f"(d) : "memory");
}
__device__ __forceinline__ uint32_t lds1(uint32_t addr) { uint32_t v; asm volatile("ld.shared.u32 %0, [%1];" : "=r"(v) : "r"(addr)); return v; }
__device__ __forceinline__ float2 lds2f(uint32_t addr) { float2 v; asm volatile("ld.shared.v2.f32 {%0,%1}, [%2];" : "=f"(v.x), "=f"(v.y) : "r"(addr)); return v; }
__device__ __forceinline__ uint4 lds4(uint32_t addr) {
  uint4 v; asm volatile("ld.shared.v4.u32 {%0,%1,%2,%3}, [%4];" : "=r"(v.x), "=r"(v.y), "=r"(v.z), "=r"(v.w) : "r"(addr)); return v;
}
__device__ __forceinline__ float4 lds4f(uint32_t addr) {
  float4 v; asm volatile("ld.shared.v4.f32 {%0,%1,%2,%3}, [%4];" : "=f"(v.x), "=f"(v.y), "=f"(v.z), "=f"(v.w) : "r"(addr)); return v;
}
__device__ __forceinline__ void mbar_init(uint32_t bar, int count) {
  asm volatile("mbarrier.init.shared::cta.b64 [%0], %1;" :: "r"(bar), "r"(count) : "memory");
}
__device__ __forceinline__ void mbar_arrive(uint32_t bar) {
  asm volatile("mbarrier.arrive.shared::cta.b64 _, [%0];" :: "r"(bar) : "memory");
}
__device__ __forceinline__ void mbar_arrive_remote(uint32_t bar) {
  asm volatile("mbarrier.arrive.shared::cluster.b64 _, [%0];" :: "r"(bar) : "memory");
}
__device__ __forceinline__ void mbar_arrive_tx(uint32_t bar, uint32_t tx) {
  asm volatile("mbarrier.arrive.expect_tx.shared::cta.b64 _, [%0], %1;" :: "r"(bar), "r"(tx) : "memory");
}
__device__ __forceinline__ void mbar_wait(uint32_t bar, uint32_t parity) {
  asm volatile("{\n.reg .pred p;\n.reg .u32 c;\nmov.u32 c, 0;\n"
               "LW:\nmbarrier.try_wait.parity.shared::cta.b64 p, [%0], %1;\n@p bra.uni LD;\n"
               "add.u32 c, c, 1;\nsetp.lt.u32 p, c, 65536;\n@p bra.uni LW;\nLD:\n}"
               :: "r"(bar), "r"(parity) : "memory");
}
__device__ __forceinline__ uint32_t mapa(uint32_t addr, uint32_t rank) {
  uint32_t r;
  asm volatile("mapa.shared::cluster.u32 %0, %1, %2;" : "=r"(r) : "r"(addr), "r"(rank));
  return r;
}
__device__ __forceinline__ void st_async1(uint32_t addr, uint32_t v, uint32_t bar) {
  asm volatile("st.async.weak.shared::cluster.mbarrier::complete_tx::bytes.b32 [%0], %1, [%2];" :: "r"(addr), "r"(v), "r"(bar) : "memory");
}
__device__ __forceinline__ void st_async2(uint32_t addr, float a, float b, uint32_t bar) {
  asm volatile("st.async.weak.shared::cluster.mbarrier::complete_tx::bytes.v2.f32 [%0], {%1,%2}, [%3];" :: "r"(addr), "f"(a), "f"(b), "r"(bar) : "memory");
}
__device__ __forceinline__ void st_async4(uint32_t addr, float a, float b, float c, float d, uint32_t bar) {
  asm volatile("st.async.weak.shared::cluster.mbarrier::complete_tx::bytes.v4.f32 [%0], {%1,%2,%3,%4}, [%5];" :: "r"(addr), "f"(a), "f"(b), "f"(c), "f"(d), "r"(bar) : "memory");
}
__device__ __forceinline__ void cluster_sync() {
  asm volatile("barrier.cluster.arrive.release.aligned;\nbarrier.cluster.wait.acquire.aligned;" ::: "memory");
}
__device__ __forceinline__ void fence_async_smem() { asm volatile("fence.proxy.async.shared::cta;" ::: "memory"); }
__device__ __forceinline__ void fence_async_all() { asm volatile("fence.proxy.async;" ::: "memory"); }
__device__ __forceinline__ void bulk_g2s(uint32_t dst, const void* src, uint32_t bytes, uint32_t bar) {
  asm volatile("cp.async.bulk.shared::cluster.global.mbarrier::complete_tx::bytes [%0], [%1], %2, [%3];"
               :: "r"(dst), "l"(src), "r"(bytes), "r"(bar) : "memory");
}
#define HINT 0
__device__ __forceinline__ uint64_t pol_first() { uint64_t p; asm volatile("createpolicy.fractional.L2::evict_first.b64 %0, 1.0;" : "=l"(p)); return p; }
__device__ __forceinline__ uint64_t pol_last() { uint64_t p; asm volatile("createpolicy.fractional.L2::evict_last.b64 %0, 1.0;" : "=l"(p)); return p; }
__device__ __forceinline__ void bulk_g2s_h(uint32_t dst, const void* src, uint32_t bytes, uint32_t bar, uint64_t pol) {
  asm volatile("cp.async.bulk.shared::cluster.global.mbarrier::complete_tx::bytes.L2::cache_hint [%0], [%1], %2, [%3], %4;"
               :: "r"(dst), "l"(src), "r"(bytes), "r"(bar), "l"(pol) : "memory");
}
__device__ __forceinline__ void stg4h(void* p, uint32_t a, uint32_t b, uint32_t c, uint32_t d) {
  if (HINT & 4) asm volatile("st.global.L2::cache_hint.v4.u32 [%0], {%1,%2,%3,%4}, %5;" :: "l"(p), "r"(a), "r"(b), "r"(c), "r"(d), "l"(pol_last()) : "memory");
  else asm volatile("st.global.v4.u32 [%0], {%1,%2,%3,%4};" :: "l"(p), "r"(a), "r"(b), "r"(c), "r"(d) : "memory");
}
__device__ __forceinline__ void bulk_g2s_mc(uint32_t dst, const void* src, uint32_t bytes, uint32_t bar, uint16_t mask) {
  asm volatile("cp.async.bulk.shared::cluster.global.mbarrier::complete_tx::bytes.multicast::cluster [%0], [%1], %2, [%3], %4;"
               :: "r"(dst), "l"(src), "r"(bytes), "r"(bar), "h"(mask) : "memory");
}
__device__ __forceinline__ void bulk_s2s(uint32_t dst_remote, uint32_t src, uint32_t bytes, uint32_t bar_remote) {
  asm volatile("cp.async.bulk.shared::cluster.shared::cta.mbarrier::complete_tx::bytes [%0], [%1], %2, [%3];"
               :: "r"(dst_remote), "r"(src), "r"(bytes), "r"(bar_remote) : "memory");
}
__device__ __forceinline__ float bf16r(float x) { return __bfloat162float(__float2bfloat16_rn(x)); }
__device__ __forceinline__ uint32_t pack_bf16(float lo, float hi) {
  uint32_t r;
  asm("cvt.rn.bf16x2.f32 %0, %1, %2;" : "=r"(r) : "f"(hi), "f"(lo));
  return r;
}
__device__ __forceinline__ uint64_t mkdesc(uint32_t saddr, uint32_t lbo, uint32_t sbo, int swz) {
  uint64_t d = 0;
  d |= (uint64_t)((saddr & 0x3FFFF) >> 4);
  d |= (uint64_t)((lbo & 0x3FFFF) >> 4) << 16;
  d |= (uint64_t)((sbo & 0x3FFFF) >> 4) << 32;
  d |= (uint64_t)swz << 62;
  return d;
}
#define WG_FENCE() asm volatile("wgmma.fence.sync.aligned;" ::: "memory")
#define WG_COMMIT() asm volatile("wgmma.commit_group.sync.aligned;" ::: "memory")
#define WG_WAIT0() asm volatile("wgmma.wait_group.sync.aligned 0;" ::: "memory")
template <int TB>
__device__ __forceinline__ void rs32(float* d, const uint32_t* a, uint64_t b) {
  asm volatile("wgmma.mma_async.sync.aligned.m64n32k16.f32.bf16.bf16 {%0,%1,%2,%3,%4,%5,%6,%7,%8,%9,%10,%11,%12,%13,%14,%15}, {%16,%17,%18,%19}, %20, 1, 1, 1, %21;"
    : "+f"(d[0]), "+f"(d[1]), "+f"(d[2]), "+f"(d[3]), "+f"(d[4]), "+f"(d[5]), "+f"(d[6]), "+f"(d[7]),
      "+f"(d[8]), "+f"(d[9]), "+f"(d[10]), "+f"(d[11]), "+f"(d[12]), "+f"(d[13]), "+f"(d[14]), "+f"(d[15])
    : "r"(a[0]), "r"(a[1]), "r"(a[2]), "r"(a[3]), "l"(b), "n"(TB));
}
template <int TA, int TB>
__device__ __forceinline__ void ss32(float* d, uint64_t a, uint64_t b) {
  asm volatile("wgmma.mma_async.sync.aligned.m64n32k16.f32.bf16.bf16 {%0,%1,%2,%3,%4,%5,%6,%7,%8,%9,%10,%11,%12,%13,%14,%15}, %16, %17, 1, 1, 1, %18, %19;"
    : "+f"(d[0]), "+f"(d[1]), "+f"(d[2]), "+f"(d[3]), "+f"(d[4]), "+f"(d[5]), "+f"(d[6]), "+f"(d[7]),
      "+f"(d[8]), "+f"(d[9]), "+f"(d[10]), "+f"(d[11]), "+f"(d[12]), "+f"(d[13]), "+f"(d[14]), "+f"(d[15])
    : "l"(a), "l"(b), "n"(TA), "n"(TB));
}

template <int TB>
__device__ __forceinline__ void rs32z(float* d, const uint32_t* a, uint64_t b) {
  asm volatile("wgmma.mma_async.sync.aligned.m64n32k16.f32.bf16.bf16 {%0,%1,%2,%3,%4,%5,%6,%7,%8,%9,%10,%11,%12,%13,%14,%15}, {%16,%17,%18,%19}, %20, 0, 1, 1, %21;"
    : "+f"(d[0]), "+f"(d[1]), "+f"(d[2]), "+f"(d[3]), "+f"(d[4]), "+f"(d[5]), "+f"(d[6]), "+f"(d[7]),
      "+f"(d[8]), "+f"(d[9]), "+f"(d[10]), "+f"(d[11]), "+f"(d[12]), "+f"(d[13]), "+f"(d[14]), "+f"(d[15])
    : "r"(a[0]), "r"(a[1]), "r"(a[2]), "r"(a[3]), "l"(b), "n"(TB));
}
template <int TA, int TB>
__device__ __forceinline__ void ss32z(float* d, uint64_t a, uint64_t b) {
  asm volatile("wgmma.mma_async.sync.aligned.m64n32k16.f32.bf16.bf16 {%0,%1,%2,%3,%4,%5,%6,%7,%8,%9,%10,%11,%12,%13,%14,%15}, %16, %17, 0, 1, 1, %18, %19;"
    : "+f"(d[0]), "+f"(d[1]), "+f"(d[2]), "+f"(d[3]), "+f"(d[4]), "+f"(d[5]), "+f"(d[6]), "+f"(d[7]),
      "+f"(d[8]), "+f"(d[9]), "+f"(d[10]), "+f"(d[11]), "+f"(d[12]), "+f"(d[13]), "+f"(d[14]), "+f"(d[15])
    : "l"(a), "l"(b), "n"(TA), "n"(TB));
}

__device__ __forceinline__ void ln_rows(uint32_t (&xw)[10], uint32_t (&xw1)[10], const int row0, const int lane) {
#pragma unroll 1
  for (int ps = 0; ps < 4; ps++) {
    float s = 0.f;
#pragma unroll
    for (int i = 0; i < 10; i++) s += __uint_as_float(xw[i] << 16) + __uint_as_float(xw[i] & 0xffff0000u);
#pragma unroll
    for (int m = 16; m; m >>= 1) s += __shfl_xor_sync(0xffffffffu, s, m);
    const float mean = s * (1.f / 640.f);
    float q = 0.f;
#pragma unroll
    for (int i = 0; i < 10; i++) {
      const float d0 = __uint_as_float(xw[i] << 16) - mean, d1 = __uint_as_float(xw[i] & 0xffff0000u) - mean;
      q = fmaf(d0, d0, q); q = fmaf(d1, d1, q);
    }
#pragma unroll
    for (int m = 16; m; m >>= 1) q += __shfl_xor_sync(0xffffffffu, q, m);
    const float var = bf16r(q * (1.f / 640.f));
    const float mb = bf16r(mean);
    const float inv = __frcp_rn(bf16r(__fsqrt_rn(bf16r(var + 1e-5f))));
    const int seg = row0 >> 5, r = (row0 & 31) + 2 * (ps & 1);
    const int fg = ((r >> 3) << 1) | (r & 1), fw = (r >> 2) & 1;
    uint32_t* dx = reinterpret_cast<uint32_t*>(g_xnT) + seg * 10240 + r * 32 + (((lane >> 2) ^ (r & 7)) << 2) + (lane & 3);
    uint2* dy = reinterpret_cast<uint2*>(g_y4) + (((seg * 2 + fw) * 40 + (lane >> 3)) * 32 + fg * 4 + (lane & 3)) * 2 + ((lane >> 2) & 1);
#pragma unroll
    for (int i = 0; i < 10; i++) {
      const uint32_t d = pack_bf16(__uint_as_float(xw[i] << 16) - mb, __uint_as_float(xw[i] & 0xffff0000u) - mb);
      const uint32_t o = pack_bf16(__uint_as_float(d << 16) * inv, __uint_as_float(d & 0xffff0000u) * inv);
      xw[i] = xw1[i]; xw1[i] = o;
      if (ps < 2) dx[i * 1024] = o;
      if (ps == 3) dy[i * 256] = make_uint2(xw[i], o);
    }
  }
}

__device__ __forceinline__ void rs192(float* d, const uint4& a, uint64_t b) {
  asm volatile("wgmma.mma_async.sync.aligned.m64n192k16.f32.bf16.bf16 {%0,%1,%2,%3,%4,%5,%6,%7,%8,%9,%10,%11,%12,%13,%14,%15,%16,%17,%18,%19,%20,%21,%22,%23,%24,%25,%26,%27,%28,%29,%30,%31,%32,%33,%34,%35,%36,%37,%38,%39,%40,%41,%42,%43,%44,%45,%46,%47,%48,%49,%50,%51,%52,%53,%54,%55,%56,%57,%58,%59,%60,%61,%62,%63,%64,%65,%66,%67,%68,%69,%70,%71,%72,%73,%74,%75,%76,%77,%78,%79,%80,%81,%82,%83,%84,%85,%86,%87,%88,%89,%90,%91,%92,%93,%94,%95}, {%96,%97,%98,%99}, %100, 1, 1, 1, 1;"
    : "+f"(d[0]), "+f"(d[1]), "+f"(d[2]), "+f"(d[3]), "+f"(d[4]), "+f"(d[5]), "+f"(d[6]), "+f"(d[7]),
      "+f"(d[8]), "+f"(d[9]), "+f"(d[10]), "+f"(d[11]), "+f"(d[12]), "+f"(d[13]), "+f"(d[14]), "+f"(d[15]),
      "+f"(d[16]), "+f"(d[17]), "+f"(d[18]), "+f"(d[19]), "+f"(d[20]), "+f"(d[21]), "+f"(d[22]), "+f"(d[23]),
      "+f"(d[24]), "+f"(d[25]), "+f"(d[26]), "+f"(d[27]), "+f"(d[28]), "+f"(d[29]), "+f"(d[30]), "+f"(d[31]),
      "+f"(d[32]), "+f"(d[33]), "+f"(d[34]), "+f"(d[35]), "+f"(d[36]), "+f"(d[37]), "+f"(d[38]), "+f"(d[39]),
      "+f"(d[40]), "+f"(d[41]), "+f"(d[42]), "+f"(d[43]), "+f"(d[44]), "+f"(d[45]), "+f"(d[46]), "+f"(d[47]),
      "+f"(d[48]), "+f"(d[49]), "+f"(d[50]), "+f"(d[51]), "+f"(d[52]), "+f"(d[53]), "+f"(d[54]), "+f"(d[55]),
      "+f"(d[56]), "+f"(d[57]), "+f"(d[58]), "+f"(d[59]), "+f"(d[60]), "+f"(d[61]), "+f"(d[62]), "+f"(d[63]),
      "+f"(d[64]), "+f"(d[65]), "+f"(d[66]), "+f"(d[67]), "+f"(d[68]), "+f"(d[69]), "+f"(d[70]), "+f"(d[71]),
      "+f"(d[72]), "+f"(d[73]), "+f"(d[74]), "+f"(d[75]), "+f"(d[76]), "+f"(d[77]), "+f"(d[78]), "+f"(d[79]),
      "+f"(d[80]), "+f"(d[81]), "+f"(d[82]), "+f"(d[83]), "+f"(d[84]), "+f"(d[85]), "+f"(d[86]), "+f"(d[87]),
      "+f"(d[88]), "+f"(d[89]), "+f"(d[90]), "+f"(d[91]), "+f"(d[92]), "+f"(d[93]), "+f"(d[94]), "+f"(d[95])
    : "r"(a.x), "r"(a.y), "r"(a.z), "r"(a.w), "l"(b));
}

__device__ __forceinline__ void rs128(float* d, const uint4& a, uint64_t b) {
  asm volatile("wgmma.mma_async.sync.aligned.m64n128k16.f32.bf16.bf16 {%0,%1,%2,%3,%4,%5,%6,%7,%8,%9,%10,%11,%12,%13,%14,%15,%16,%17,%18,%19,%20,%21,%22,%23,%24,%25,%26,%27,%28,%29,%30,%31,%32,%33,%34,%35,%36,%37,%38,%39,%40,%41,%42,%43,%44,%45,%46,%47,%48,%49,%50,%51,%52,%53,%54,%55,%56,%57,%58,%59,%60,%61,%62,%63}, {%64,%65,%66,%67}, %68, 1, 1, 1, 1;"
    : "+f"(d[0]), "+f"(d[1]), "+f"(d[2]), "+f"(d[3]), "+f"(d[4]), "+f"(d[5]), "+f"(d[6]), "+f"(d[7]),
      "+f"(d[8]), "+f"(d[9]), "+f"(d[10]), "+f"(d[11]), "+f"(d[12]), "+f"(d[13]), "+f"(d[14]), "+f"(d[15]),
      "+f"(d[16]), "+f"(d[17]), "+f"(d[18]), "+f"(d[19]), "+f"(d[20]), "+f"(d[21]), "+f"(d[22]), "+f"(d[23]),
      "+f"(d[24]), "+f"(d[25]), "+f"(d[26]), "+f"(d[27]), "+f"(d[28]), "+f"(d[29]), "+f"(d[30]), "+f"(d[31]),
      "+f"(d[32]), "+f"(d[33]), "+f"(d[34]), "+f"(d[35]), "+f"(d[36]), "+f"(d[37]), "+f"(d[38]), "+f"(d[39]),
      "+f"(d[40]), "+f"(d[41]), "+f"(d[42]), "+f"(d[43]), "+f"(d[44]), "+f"(d[45]), "+f"(d[46]), "+f"(d[47]),
      "+f"(d[48]), "+f"(d[49]), "+f"(d[50]), "+f"(d[51]), "+f"(d[52]), "+f"(d[53]), "+f"(d[54]), "+f"(d[55]),
      "+f"(d[56]), "+f"(d[57]), "+f"(d[58]), "+f"(d[59]), "+f"(d[60]), "+f"(d[61]), "+f"(d[62]), "+f"(d[63])
    : "r"(a.x), "r"(a.y), "r"(a.z), "r"(a.w), "l"(b));
}
__device__ __forceinline__ uint4 ldg_nc4(const uint4* p) {
  uint4 v;
  asm volatile("ld.global.nc.L1::no_allocate.v4.u32 {%0,%1,%2,%3}, [%4];" : "=r"(v.x), "=r"(v.y), "=r"(v.z), "=r"(v.w) : "l"(p));
  return v;
}
__device__ __forceinline__ uint4 ldg_cg4(const uint4* p) {
  uint4 v;
  asm volatile("ld.global.cg.v4.u32 {%0,%1,%2,%3}, [%4];" : "=r"(v.x), "=r"(v.y), "=r"(v.z), "=r"(v.w) : "l"(p) : "memory");
  return v;
}
__device__ __forceinline__ void tma3_mc(uint32_t dst, const CUtensorMap* tm, int c0, int c1, int c2, uint32_t bar, uint16_t mask) {
  asm volatile("cp.async.bulk.tensor.3d.shared::cluster.global.mbarrier::complete_tx::bytes.multicast::cluster [%0], [%1, {%2,%3,%4}], [%5], %6;"
               :: "r"(dst), "l"(tm), "r"(c0), "r"(c1), "r"(c2), "r"(bar), "h"(mask) : "memory");
}
#define WG_WAIT1() asm volatile("wgmma.wait_group.sync.aligned 1;" ::: "memory")

__device__ __forceinline__ float bf_lo(uint32_t w) { return __uint_as_float(w << 16); }
__device__ __forceinline__ float bf_hi(uint32_t w) { return __uint_as_float(w & 0xffff0000u); }
__device__ __forceinline__ float gelu_t(float v) {
  const float u = v * fmaf(v * v, 0.7978845608028654f * 0.044715f, 0.7978845608028654f);
  float th; asm("tanh.approx.f32 %0, %1;" : "=f"(th) : "f"(u));
  const float hv = 0.5f * v;
  return fmaf(hv, th, hv);
}
__device__ __forceinline__ float silu_f(float v) { return __fdividef(v, 1.f + __expf(-v)); }

#define NML 32
__device__ __forceinline__ void mlp1_part(const CUtensorMap* tmW1, const bf16* __restrict__ b1, const uint32_t sb, const int cl) {
  constexpr uint32_t SB = 24576;
  const uint32_t bars = sb + 8 * SB;
  const int tid = threadIdx.x, lane = tid & 31, warp = __shfl_sync(0xffffffffu, tid >> 5, 0), rank = blockIdx.x & 1;
  if (warp >= 8) {
    asm volatile("setmaxnreg.dec.sync.aligned.u32 40;");
    if (tid == 256) {
      int k = 0, nb = 0;
#pragma unroll 1
      for (int it = 0; it < NML * 10; it++) {
        const int slot = it & 7;
        mbar_wait(bars + 64 + slot * 8, ((it >> 3) & 1) ^ 1);
        mbar_arrive_tx(bars + slot * 8, SB);
        tma3_mc(sb + slot * SB + rank * 12288, tmW1, 0, k * 64 + rank * 32, nb * 3, bars + slot * 8, 3);
        if (++k == 10) { k = 0; nb = (nb + 1) & 7; }
      }
    }
  } else {
    asm volatile("setmaxnreg.inc.sync.aligned.u32 232;");
    const uint32_t bars_peer = mapa(bars, rank ^ 1);
    const uint4* A = g_y4 + (size_t)((cl * 8 + rank) * 8 + warp) * 1280 + lane;
    uint4 a[5][4];
#pragma unroll
    for (int b = 0; b < 5; b++)
#pragma unroll
      for (int k = 0; k < 4; k++) a[b][k] = ldg_cg4(A + b * 128 + k * 32);
    int it = 0;
#pragma unroll 1
    for (int i = 0; i < NML; i++) {
      const int mb = (cl * 4 + (i >> 3)) * 2 + rank, nb = i & 7;
      const uint4* An = (i & 7) == 7 && i < 31 ? A + 16 * 1280 : A;
      float acc[96];
#pragma unroll
      for (int k = 0; k < 96; k++) acc[k] = 0.f;
#pragma unroll 1
      for (int s0 = 0; s0 < 2; s0++) {
        const uint4* Ap = s0 ? An : A + 640;
#pragma unroll
        for (int b = 0; b < 5; b++) {
          const int slot = it & 7;
          mbar_wait(bars + slot * 8, (it >> 3) & 1);
          const uint64_t bd = mkdesc(sb + slot * SB, 4096, 1024, 1);
          WG_FENCE();
#pragma unroll
          for (int k = 0; k < 4; k++) rs192(acc, a[b][k], bd + (uint64_t)(((k >> 1) * 12288 + (k & 1) * 2048) >> 4));
          WG_COMMIT();
          if (b > 0 || s0) {
            WG_WAIT1();
            const int ps = (it + 7) & 7;
            if (lane == 0) mbar_arrive(bars + 64 + ps * 8);
            if (lane == 1) mbar_arrive_remote(bars_peer + 64 + ps * 8);
            const uint4* src = b ? Ap + (b - 1) * 128 : A + 640 + 512;
#pragma unroll
            for (int k = 0; k < 4; k++) a[(b + 4) % 5][k] = ldg_cg4(src + k * 32);
          }
          it++;
        }
      }
      WG_WAIT0();
      {
        const int ps = (it + 7) & 7;
        if (lane == 0) mbar_arrive(bars + 64 + ps * 8);
        if (lane == 1) mbar_arrive_remote(bars_peer + 64 + ps * 8);
#pragma unroll
        for (int k = 0; k < 4; k++) a[4][k] = ldg_cg4(An + 512 + k * 32);
      }
      A = An;
      const uint32_t* bp = reinterpret_cast<const uint32_t*>(b1 + nb * 192) + (lane & 3);
      uint4* dst = g_h4 + ((size_t)(mb * 24 + nb * 3) * 8 + warp) * 128 + lane;
#pragma unroll
      for (int j = 0; j < 12; j++) {
        uint32_t w[4];
#pragma unroll
        for (int u = 0; u < 2; u++) {
          const uint32_t bw = __ldg(bp + (2 * j + u) * 4);
          const float* d = acc + (2 * j + u) * 4;
          const uint32_t p0 = pack_bf16(d[0], d[1]), p1 = pack_bf16(d[2], d[3]);
          const uint32_t q0 = pack_bf16(bf_lo(p0) + bf_lo(bw), bf_hi(p0) + bf_hi(bw));
          const uint32_t q1 = pack_bf16(bf_lo(p1) + bf_lo(bw), bf_hi(p1) + bf_hi(bw));
          w[2 * u] = pack_bf16(gelu_t(bf_lo(q0)), gelu_t(bf_hi(q0)));
          w[2 * u + 1] = pack_bf16(gelu_t(bf_lo(q1)), gelu_t(bf_hi(q1)));
        }
        dst[(j >> 2) * 1024 + (j & 3) * 32] = make_uint4(w[0], w[1], w[2], w[3]);
      }
    }
    if (tid == 0) TLM(3);
  }
}

constexpr int FST = 4;
constexpr uint32_t FSB = 57344;
constexpr int FIN_SMEM = FST * 57344 + 1024 + 128;
#define FKA 30
#define BULKST 0
#define PFX 0
#define PFD 0
#define LIGHT 1
#define SKMAP(x) (3 - (x))
#define TPDL 60
__device__ __forceinline__ void fin_run(float* acc, int nst, int& it, uint32_t sb, uint32_t bars, int tid, uint32_t bars_peer) {
  const int lane = tid & 31;
  const uint32_t ao = sb + (tid >> 5) * 2048 + lane * 16;
  uint4 a[2][4];
  mbar_wait(bars + (it % FST) * 8, (it / FST) & 1);
#pragma unroll
  for (int k = 0; k < 4; k++) a[0][k] = lds4(ao + (it % FST) * FSB + k * 512);
  for (int s0 = 0; s0 < nst; s0 += 2) {
#pragma unroll
    for (int b = 0; b < 2; b++) {
      const int s = s0 + b;
      if (s < nst) {
        const uint64_t bd = mkdesc(sb + (it % FST) * FSB + 16384, 4096, 1024, 1);
        WG_FENCE();
#pragma unroll
        for (int k = 0; k < 4; k++) {
          const uint64_t d = bd + (uint64_t)(((k >> 1) * 20480 + (k & 1) * 2048) >> 4);
          rs192(acc, a[b][k], d);
          rs128(acc + 96, a[b][k], d + (3 * 4096 >> 4));
        }
        WG_COMMIT();
        WG_WAIT1();
        if (s > 0) {
          const int ps = (it + FST - 1) % FST;
          if (lane == 0) mbar_arrive(bars + 64 + ps * 8);
          if (lane == 1) mbar_arrive_remote(bars_peer + 64 + ps * 8);
        }
        it++;
        if (s + 1 < nst) {
          mbar_wait(bars + (it % FST) * 8, (it / FST) & 1);
#pragma unroll
          for (int k = 0; k < 4; k++) a[b ^ 1][k] = lds4(ao + (it % FST) * FSB + k * 512);
        }
      }
    }
  }
  WG_WAIT0();
  const int ps = (it + FST - 1) % FST;
  if (lane == 0) mbar_arrive(bars + 64 + ps * 8);
  if (lane == 1) mbar_arrive_remote(bars_peer + 64 + ps * 8);
}
__device__ __forceinline__ uint32_t pack_ph(float lo, float hi, uint32_t ph) {
  const uint32_t r = ((__float_as_uint(lo) + (ph ? 0u : 0x10000u)) & 0xFFFE0000u) | (ph << 16);
  return __byte_perm(r, pack_bf16(0.f, hi), 0x7632);
}
__device__ __forceinline__ uint32_t pack_phv(float lo, float hi, uint32_t ph16) {
  uint32_t r;
  asm volatile("{\n.reg .b32 t, u;\nmov.b32 t, %1;\nsub.u32 t, t, %3;\nadd.u32 t, t, 0x10000;\nand.b32 t, t, 0xFFFE0000;\nor.b32 t, t, %3;\n"
               "cvt.rn.bf16x2.f32 u, %2, %2;\nprmt.b32 %0, t, u, 0x7632;\n}" : "=r"(r) : "f"(lo), "f"(hi), "r"(ph16));
  return r;
}
__device__ __forceinline__ void ld_ph4(uint4& v, const uint4* p, uint32_t ph) {
  asm volatile("{\n.reg .pred q;\n.reg .u32 m;\nand.b32 m, %0, 1;\nsetp.ne.u32 q, m, %5;\n"
               "@q ld.relaxed.gpu.global.v4.u32 {%0,%1,%2,%3}, [%4];\n}"
               : "+r"(v.x), "+r"(v.y), "+r"(v.z), "+r"(v.w) : "l"(p), "r"(ph) : "memory");
}
__global__ void __cluster_dims__(2, 1, 1) __launch_bounds__(384, 1)
final_kernel(const __grid_constant__ CUtensorMap tmWo, const __grid_constant__ CUtensorMap tmW2,
             const bf16* __restrict__ b2, const bf16* __restrict__ x, bf16* __restrict__ out) {
  extern __shared__ uint8_t smem_raw[];
  const uint32_t sb = (smem_u32(smem_raw) + 1023u) & ~1023u, bars = sb + FST * FSB;
  const int tid = threadIdx.x, lane = tid & 31, warp = tid >> 5;
  const int rank = blockIdx.x & 1, c = blockIdx.x >> 1, mb = (c & 7) * 2 + rank, nb = (c >> 3) & 1, sk = SKMAP(c >> 4);
  if (tid == 0) { TLM(8); DBG(0); }
  const int st0 = sk * FKA, nst = sk < 3 ? FKA : 96 - 3 * FKA, tile = mb * 2 + nb;
  if (tid == 256) asm volatile("prefetch.tensormap [%0];" :: "l"(sk == 3 ? &tmW2 : &tmWo) : "memory");
  if (tid == 320) {
    for (int i = 0; i < FST; i++) { mbar_init(bars + i * 8, 1); mbar_init(bars + 64 + i * 8, 16); }
    asm volatile("fence.mbarrier_init.release.cluster;" ::: "memory");
  }
  __syncwarp();
  asm volatile("barrier.cluster.arrive.relaxed.aligned;" ::: "memory");
  if (warp != 10) asm volatile("barrier.cluster.wait.acquire.aligned;" ::: "memory");
  if (warp >= 8) {
    asm volatile("setmaxnreg.dec.sync.aligned.u32 40;");
    const int ntot = sk == 3 ? nst + 24 : nst, sw = sk == 3 ? 24 : -1;
    if (tid == 256) {
      const CUtensorMap* tm = sk == 3 ? &tmW2 : &tmWo;
      int k = (sk == 3 ? 0 : st0 * 64) + rank * 32;
      const uint32_t bo = sb + 16384 + rank * 20480;
#pragma unroll 1
      for (int it = 0; it < ntot; it++, k += 64) {
        const int slot = it % FST;
        if (it == sw) { tm = &tmWo; k = st0 * 64 + rank * 32; }
        if (it == FST) asm volatile("griddepcontrol.wait;" ::: "memory");
        mbar_wait(bars + 64 + slot * 8, ((it / FST) & 1) ^ 1);
        mbar_arrive_tx(bars + slot * 8, FSB);
        tma3_mc(bo + slot * FSB, tm, 0, k, nb * 5, bars + slot * 8, 3);
      }
    } else if (warp == 10) {
      if (lane == 0) {
      fence_async_smem();
      const uint4* A1 = g_ox4 + ((size_t)mb * 96 + st0) * 1024;
      const uint4* A = sk == 3 ? g_h4 + (size_t)mb * 24 * 1024 : A1;
      asm volatile("griddepcontrol.wait;" ::: "memory");
      TLM(16);
#pragma unroll 1
      for (int it = 0; it < ntot; it++, A += 1024) {
        const int slot = it % FST;
        if (it == sw) A = A1;
        mbar_wait(bars + 64 + slot * 8, ((it / FST) & 1) ^ 1);
        if (HINT & 2) bulk_g2s_h(sb + slot * FSB, A, 16384, bars + slot * 8, pol_first());
        else bulk_g2s(sb + slot * FSB, A, 16384, bars + slot * 8);
      }
      }
      __syncwarp();
      asm volatile("barrier.cluster.wait.acquire.aligned;" ::: "memory");
    } else if (warp == 9) {
      if (lane == 0) sts1(bars + 120, (uint32_t)(*(volatile unsigned long long*)&g_cnt / 132) & 1u);
      if (sk == 3) {
        bar_sync(1, 288);
        if (lane == 0) { __threadfence(); st_rlx1(g_flag + tile, 1u); }
      } else {
        asm volatile("griddepcontrol.wait;" ::: "memory");
        int guard = 0;
        if (lane == 0) while (ld_acq1(g_flag + tile) == 0u) { __nanosleep(500); if (++guard > SPIN_LIMIT) { g_err = 21; break; } }
      }
      __syncwarp();
      bar_arrive(2, 288);
    } else if (warp == 11) {
      asm volatile("griddepcontrol.wait;" ::: "memory");
      __nanosleep(PFD);
      const size_t xo = (size_t)(mb * 128 + lane * 4) * 640 + nb * 320 + sk * 80;
#pragma unroll 1
      for (int i = 0; i < ((PFX & 1) ? 8 : 4); i++) {
        const bf16* xp = (i < 4 ? x : out) + xo + (i & 3) * 640;
        asm volatile("prefetch.global.L2 [%0];" :: "l"(xp));
        asm volatile("prefetch.global.L2 [%0];" :: "l"(xp + 64));
        asm volatile("prefetch.global.L2 [%0];" :: "l"(xp + 79));
      }
      if (PFX & 2) {
#pragma unroll 1
        for (int i = 0; i < 20; i++) {
          const int q = i / 5;
          if (q != sk) asm volatile("prefetch.global.L2 [%0];" :: "l"(g_part + ((size_t)tile * 16 + q * 4 + sk) * 1280 + (i - q * 5) * 256 + lane * 8));
        }
      }
      if ((PFX & 4) && sk == 3) {
#pragma unroll 1
        for (int i = 0; i < 20; i++) asm volatile("prefetch.global.L2 [%0];" :: "l"(g_gt4 + (size_t)tile * 5120 + i * 256 + lane * 8));
      }
    }
  } else {
    asm volatile("setmaxnreg.inc.sync.aligned.u32 232;");
    asm volatile("griddepcontrol.wait;" ::: "memory");
    float acc[160];
    const int mt = mb * 8 + warp;
    const uint32_t bars_peer = mapa(bars, rank ^ 1);
    uint4* gt = g_gt4 + (size_t)tile * 20 * 256 + tid;
    int it = 0;
#pragma unroll 1
    for (int ph = sk == 3 ? 0 : 1; ; ph++) {
#pragma unroll
      for (int i = 0; i < 160; i++) acc[i] = 0.f;
      fin_run(acc, ph ? nst : 24, it, sb, bars, tid, bars_peer);
      if (ph) break;
#pragma unroll
      for (int j = 0; j < 20; j++) {
        const float* d = acc + j * 8;
        gt[j * 256] = make_uint4(pack_bf16(d[0], d[1]), pack_bf16(d[2], d[3]), pack_bf16(d[4], d[5]), pack_bf16(d[6], d[7]));
      }
      bar_arrive(1, 288);
    }
    if (tid == 0) { TLM(9); DBG(1); }
    uint4* pt = g_part + (size_t)tile * 16 * 5 * 256 + warp * 160 + lane;
    bar_sync(2, 288);
    const uint32_t ep = lds1(bars + 120);
#pragma unroll
    for (int q = 0; q < 4; q++) {
      if (q != sk) {
#pragma unroll
        for (int i = 0; i < 5; i++) {
          const float* d = acc + q * 40 + i * 8;
          st_rlx4(reinterpret_cast<uint32_t*>(pt + (q * 4 + sk) * 1280 + i * 32),
                  pack_phv(d[0], d[1], ep << 16), pack_bf16(d[2], d[3]), pack_bf16(d[4], d[5]), pack_bf16(d[6], d[7]));
        }
      }
    }
    float own[40];
#pragma unroll
    for (int i = 0; i < 40; i++) own[i] = sk == 0 ? acc[i] : sk == 1 ? acc[40 + i] : sk == 2 ? acc[80 + i] : acc[120 + i];
    uint4 gw[5];
#pragma unroll
    for (int j = 0; j < 5; j++) gw[j] = ldg_cg4(gt + (sk * 5 + j) * 256);
    const int r0 = (mt >> 1) * 32 + 8 * (lane >> 3) + 4 * (mt & 1) + ((lane >> 2) & 1);
    const size_t o0 = (size_t)r0 * 640 + nb * 320 + sk * 80 + 2 * (lane & 3);
    uint32_t xv[20], bw[10];
#pragma unroll
    for (int i = 0; i < 10; i++) {
      bw[i] = __ldg(reinterpret_cast<const uint32_t*>(b2 + nb * 320 + sk * 80) + (lane & 3) + i * 4);
      xv[2 * i] = __ldg(reinterpret_cast<const uint32_t*>(x + o0 + i * 8));
      xv[2 * i + 1] = __ldg(reinterpret_cast<const uint32_t*>(x + o0 + 2 * 640 + i * 8));
    }
    uint32_t g[20];
#pragma unroll
    for (int i = 0; i < 20; i++) {
      const uint4 q4 = gw[i >> 2];
      const uint32_t p = (i & 3) == 0 ? q4.x : (i & 3) == 1 ? q4.y : (i & 3) == 2 ? q4.z : q4.w, b = bw[i >> 1];
      const uint32_t q = pack_bf16(bf_lo(p) + bf_lo(b), bf_hi(p) + bf_hi(b));
      g[i] = pack_bf16(silu_f(bf_lo(q)), silu_f(bf_hi(q)));
    }
    uint4 v[3][5];
    {
      int guard = 0;
#pragma unroll 1
      while (true) {
        uint32_t bad = 0;
#pragma unroll
        for (int j = 0; j < 3; j++) bad |= ld_rlx1(reinterpret_cast<const uint32_t*>(pt + (sk * 4 + j + (j >= sk)) * 1280 + 128)) ^ ep;
        if (!(bad & 1u)) break;
        if (++guard > SPIN_LIMIT) { g_err = 20; break; }
      }
#pragma unroll 1
      while (true) {
        uint32_t bad = 0;
#pragma unroll
        for (int j = 0; j < 3; j++) {
          const int src = j + (j >= sk);
#pragma unroll
          for (int i = 0; i < 5; i++) v[j][i] = ld_rlx4(reinterpret_cast<const uint32_t*>(pt + (sk * 4 + src) * 1280 + i * 32));
        }
#pragma unroll
        for (int j = 0; j < 15; j++) bad |= v[j / 5][j % 5].x ^ ep;
        if (!(bad & 1u)) break;
        if (++guard > SPIN_LIMIT) { g_err = 20; break; }
      }
    }
    if (tid == 0) { TLM(10); DBG(2); }
#pragma unroll
    for (int i = 0; i < 10; i++) {
      uint32_t u0[3], u1[3];
#pragma unroll
      for (int j = 0; j < 3; j++) { u0[j] = (i & 1) ? v[j][i >> 1].z : v[j][i >> 1].x; u1[j] = (i & 1) ? v[j][i >> 1].w : v[j][i >> 1].y; }
      const float s0_ = (own[4 * i] + bf_lo(u0[0])) + (bf_lo(u0[1]) + bf_lo(u0[2]));
      const float s1_ = (own[4 * i + 1] + bf_hi(u0[0])) + (bf_hi(u0[1]) + bf_hi(u0[2]));
      const float s2_ = (own[4 * i + 2] + bf_lo(u1[0])) + (bf_lo(u1[1]) + bf_lo(u1[2]));
      const float s3_ = (own[4 * i + 3] + bf_hi(u1[0])) + (bf_hi(u1[1]) + bf_hi(u1[2]));
      const uint32_t g0 = g[2 * i], g1 = g[2 * i + 1];
      const uint32_t x0 = xv[2 * i], x1 = xv[2 * i + 1];
      const uint32_t s0 = pack_bf16(s0_, s1_), s1 = pack_bf16(s2_, s3_);
      const uint32_t m0 = pack_bf16(bf_lo(s0) * bf_lo(g0), bf_hi(s0) * bf_hi(g0));
      const uint32_t m1 = pack_bf16(bf_lo(s1) * bf_lo(g1), bf_hi(s1) * bf_hi(g1));
      *reinterpret_cast<uint32_t*>(out + o0 + i * 8) = pack_bf16(bf_lo(x0) + bf_lo(m0), bf_hi(x0) + bf_hi(m0));
      *reinterpret_cast<uint32_t*>(out + o0 + 2 * 640 + i * 8) = pack_bf16(bf_lo(x1) + bf_lo(m1), bf_hi(x1) + bf_hi(m1));
    }
    if (tid == 0) TLM(11);
  }
  cluster_sync();
}

constexpr uint32_t QK_T2 = 0, QK_XN = 81920, QK_QX = 122880, QK_R = 147456, QK_PB = 159744,
                   QK_MEM = 176128, QK_S = 186368, QK_SCX = 189440, QK_BS = 194560, QK_RED = 215040;
constexpr uint32_t VO_MID = 0, VO_O4 = 40960, VO_OP = 65536, VO_XN = 81920, VO_VX = 122880, VO_XM = 172032,
                   VO_MEM = 188416, VO_VM = 198656, VO_PX = 207872, VO_FX = 210944, VO_PBR = 219136, VO_RED = 227328;
constexpr uint32_t BARS = 231552;
constexpr int CHAIN_SMEM = BARS + 512;
constexpr uint32_t B_XNF = 64, B_XNE = 80, B_TR = 160;
constexpr uint32_t B_S = 8, B_X = 16;
constexpr uint32_t B_PC = 8, B_VXR = 16, B_PB = 32, B_PXF = 112;
#define G_Q 2450
#define G_V 3600
#define G_S 2500
#define GATE_Z 200
#define GATE_PV 600
#define NPRE 5
#define NPRV 5
#define PMAX 12000

#define ZE 1
#define N1 10
#define NW1 1
#define PD2 0
#define FP 0
#define W1S 1
#define NT2 0
#define NB4 0
#define PMW 0
#define GATE_ZQ 300
struct ChainParams { const bf16 *Wq, *Wk, *Wv, *Wo, *x, *mem0, *b1; };
constexpr float SCALE = 0.07216878364870322f;

__device__ __forceinline__ uint32_t clk32() { uint32_t c; asm volatile("mov.u32 %0, %%clock;" : "=r"(c) :: "memory"); return c; }
__device__ __forceinline__ float ex2f(float x) { float y; asm("ex2.approx.ftz.f32 %0, %1;" : "=f"(y) : "f"(x)); return y; }
__device__ __forceinline__ float rcpf(float x) { float y; asm("rcp.approx.ftz.f32 %0, %1;" : "=f"(y) : "f"(x)); return y; }
__device__ __forceinline__ void softmax_row(float (&s)[5][2], uint32_t (&w)[5]) {
  float m = fmaxf(fmaxf(fmaxf(s[0][0], s[0][1]), fmaxf(s[1][0], s[1][1])),
                  fmaxf(fmaxf(fmaxf(s[2][0], s[2][1]), fmaxf(s[3][0], s[3][1])), fmaxf(s[4][0], s[4][1])));
  m = fmaxf(m, __shfl_xor_sync(0xffffffffu, m, 1));
  m = fmaxf(m, __shfl_xor_sync(0xffffffffu, m, 2));
  constexpr float L2E = 1.4426950408889634f;
#pragma unroll
  for (int j = 0; j < 5; j++) { s[j][0] = ex2f((s[j][0] - m) * L2E); s[j][1] = ex2f((s[j][1] - m) * L2E); }
  float sum = ((s[0][0] + s[0][1]) + (s[1][0] + s[1][1])) + (((s[2][0] + s[2][1]) + (s[3][0] + s[3][1])) + (s[4][0] + s[4][1]));
  sum += __shfl_xor_sync(0xffffffffu, sum, 1);
  sum += __shfl_xor_sync(0xffffffffu, sum, 2);
  float inv = rcpf(sum);
#pragma unroll
  for (int j = 0; j < 5; j++) w[j] = pack_bf16(s[j][0] * inv, s[j][1] * inv);
}
__device__ __forceinline__ void scale_pair(float a, float b, float& o0, float& o1) {
  uint32_t p = pack_bf16(a, b);
  uint32_t q = pack_bf16(__uint_as_float(p << 16) * SCALE, __uint_as_float(p & 0xffff0000u) * SCALE);
  o0 = __uint_as_float(q << 16); o1 = __uint_as_float(q & 0xffff0000u);
}
__device__ __forceinline__ bool mbar_test(uint32_t bar, uint32_t parity) {
  uint32_t r;
  asm volatile("{\n.reg .pred p;\nmbarrier.test_wait.parity.shared::cta.b64 p, [%1], %2;\nselp.u32 %0, 1, 0, p;\n}"
               : "=r"(r) : "r"(bar), "r"(parity) : "memory");
  return r != 0;
}
__device__ __forceinline__ bool bar_red_or(int id, bool p) {
  uint32_t r;
  asm volatile("{\n.reg .pred p, q;\nsetp.ne.u32 q, %2, 0;\nbarrier.cta.red.or.pred p, %1, 128, q;\nselp.u32 %0, 1, 0, p;\n}"
               : "=r"(r) : "r"(id), "r"((uint32_t)p) : "memory");
  return r != 0;
}
__device__ __forceinline__ uint2 lds2v(uint32_t addr) {
  uint2 v; asm volatile("ld.volatile.shared.v2.u32 {%0,%1}, [%2];" : "=r"(v.x), "=r"(v.y) : "r"(addr) : "memory"); return v;
}
__device__ __forceinline__ uint32_t movm(uint32_t a) {
  uint32_t d; asm volatile("movmatrix.sync.aligned.m8n8.trans.b16 %0, %1;" : "=r"(d) : "r"(a)); return d;
}
template <int acc>
__device__ __forceinline__ void ss40(float* d, uint64_t a, uint64_t b) {
  asm volatile("wgmma.mma_async.sync.aligned.m64n40k16.f32.bf16.bf16 {%0,%1,%2,%3,%4,%5,%6,%7,%8,%9,%10,%11,%12,%13,%14,%15,%16,%17,%18,%19}, %20, %21, %22, 1, 1, 1, 1;"
    : "+f"(d[0]), "+f"(d[1]), "+f"(d[2]), "+f"(d[3]), "+f"(d[4]), "+f"(d[5]), "+f"(d[6]), "+f"(d[7]), "+f"(d[8]), "+f"(d[9]),
      "+f"(d[10]), "+f"(d[11]), "+f"(d[12]), "+f"(d[13]), "+f"(d[14]), "+f"(d[15]), "+f"(d[16]), "+f"(d[17]), "+f"(d[18]), "+f"(d[19])
    : "l"(a), "l"(b), "n"(acc));
}

#define LAUNDER(x) asm volatile("" : "+r"(x))
__device__ __forceinline__ constexpr uint32_t xoff(int ks) { return (uint32_t)(((ks >> 2) * 4096 + (ks & 3) * 32) >> 4); }
#define ROLE_IDS() \
  uint32_t bx_; asm volatile("mov.u32 %0, %%ctaid.x;" : "=r"(bx_)); \
  const int rank = bx_ & 1, h = bx_ >> 2; (void)rank; (void)h
#define IDS() \
  uint32_t tx_ = tid; LAUNDER(tx_); \
  const int ln = tx_ & 31, warp = (tx_ >> 5) & 3, wl = tx_ & 127, rank = blockIdx.x & 1, h = blockIdx.x >> 2; \
  (void)ln; (void)warp; (void)wl; (void)rank; (void)h
#define A_OFF ((uint32_t)(((ln & 7) + ((ln >> 4) & 1) * 8) * 128 + (((2 * warp + ((ln >> 3) & 1)) ^ (ln & 7)) << 4)))
#define WARP_ARRIVE(bar) do { __syncwarp(); if (ln == 0) mbar_arrive(bar); } while (0)

__device__ __forceinline__ uint32_t lds1v(uint32_t addr) {
  uint32_t v; asm volatile("ld.volatile.shared.u32 %0, [%1];" : "=r"(v) : "r"(addr) : "memory"); return v;
}
template <int TB, int SC>
__device__ __forceinline__ void rsA(const uint32_t* a, uint64_t b) {
  asm volatile("wgmma.mma_async.sync.aligned.m64n32k16.f32.bf16.bf16 {acc0,acc1,acc2,acc3,acc4,acc5,acc6,acc7,acc8,acc9,acc10,acc11,acc12,acc13,acc14,acc15}, {%0,%1,%2,%3}, %4, %5, 1, 1, %6;"
    :: "r"(a[0]), "r"(a[1]), "r"(a[2]), "r"(a[3]), "l"(b), "n"(SC), "n"(TB));
}
template <int TA, int TB, int SC>
__device__ __forceinline__ void ssA(uint64_t a, uint64_t b) {
  asm volatile("wgmma.mma_async.sync.aligned.m64n32k16.f32.bf16.bf16 {acc0,acc1,acc2,acc3,acc4,acc5,acc6,acc7,acc8,acc9,acc10,acc11,acc12,acc13,acc14,acc15}, %0, %1, %2, 1, 1, %3, %4;"
    :: "l"(a), "l"(b), "n"(SC), "n"(TA), "n"(TB));
}
#define GET_D() float d[16]; asm volatile("mov.f32 %0, acc0; mov.f32 %1, acc1; mov.f32 %2, acc2; mov.f32 %3, acc3; mov.f32 %4, acc4; mov.f32 %5, acc5;" \
    "mov.f32 %6, acc6; mov.f32 %7, acc7; mov.f32 %8, acc8; mov.f32 %9, acc9; mov.f32 %10, acc10; mov.f32 %11, acc11;" \
    "mov.f32 %12, acc12; mov.f32 %13, acc13; mov.f32 %14, acc14; mov.f32 %15, acc15;" \
    : "=f"(d[0]), "=f"(d[1]), "=f"(d[2]), "=f"(d[3]), "=f"(d[4]), "=f"(d[5]), "=f"(d[6]), "=f"(d[7]), \
      "=f"(d[8]), "=f"(d[9]), "=f"(d[10]), "=f"(d[11]), "=f"(d[12]), "=f"(d[13]), "=f"(d[14]), "=f"(d[15]))
#define WAIT_D() WG_WAIT0(); GET_D()
#define ZERO_ACC() asm volatile("mov.f32 acc0, 0f00000000; mov.f32 acc1, acc0; mov.f32 acc2, acc0; mov.f32 acc3, acc0; mov.f32 acc4, acc0; mov.f32 acc5, acc0;" \
    "mov.f32 acc6, acc0; mov.f32 acc7, acc0; mov.f32 acc8, acc0; mov.f32 acc9, acc0; mov.f32 acc10, acc0; mov.f32 acc11, acc0;" \
    "mov.f32 acc12, acc0; mov.f32 acc13, acc0; mov.f32 acc14, acc0; mov.f32 acc15, acc0;")
__device__ __forceinline__ uint64_t dsc(uint32_t lo, uint32_t hi) { return ((uint64_t)hi << 32) | lo; }
constexpr uint32_t HI_128 = 0x40000040u;
constexpr uint32_t HI_64 = 0x80000020u;
#define XLO(base) uint32_t xl_ = ((base) >> 4) | 0x10000u; LAUNDER(xl_)
#define RS_X(Wx, K0, M, XN) { XLO(sb + (XN)); WG_FENCE(); \
            _Pragma("unroll") for (int ks = (K0); ks < (K0) + (M); ks++) { \
              if (ks == 0) rsA<0, 0>(Wx[ks], dsc(xl_ + xoff(ks), HI_128)); else rsA<0, 1>(Wx[ks], dsc(xl_ + xoff(ks), HI_128)); } }
#define XN_REL(j) { uint32_t tx_, bx_; asm volatile("mov.u32 %0, %%tid.x;" : "=r"(tx_)); asm volatile("mov.u32 %0, %%ctaid.x;" : "=r"(bx_)); \
            if ((tx_ & 31) == 0) { mbar_arrive(bars + B_XNE + (j) * 8); mbar_arrive_remote(mapa(bars + B_XNE + (j) * 8, (bx_ & 1) ^ 1)); } }
#define PUT_PART(addr) { _Pragma("unroll") for (int i = 0; i < 4; i++) sts4f((addr) + i * 2048, d[4 * i], d[4 * i + 1], d[4 * i + 2], d[4 * i + 3]); }
#define ADD_PART(addr) { _Pragma("unroll") for (int i = 0; i < 4; i++) { float4 o = lds4f((addr) + i * 2048); \
              d[4 * i] += o.x; d[4 * i + 1] += o.y; d[4 * i + 2] += o.z; d[4 * i + 3] += o.w; } }
#define STORE_TX(d, base) { const int fo = warp * 16 + (ln >> 2); const uint32_t qa = (base) + fo * 64 + (((ln & 3) ^ ((fo >> 1) & 3)) << 4); \
            sts4(qa, pack_bf16(d[0], d[1]), pack_bf16(d[4], d[5]), pack_bf16(d[8], d[9]), pack_bf16(d[12], d[13])); \
            sts4(qa + 512, pack_bf16(d[2], d[3]), pack_bf16(d[6], d[7]), pack_bf16(d[10], d[11]), pack_bf16(d[14], d[15])); }
#define STORE_T(base) STORE_TX(d, base)
#define XN_RELEASE(j) { if (ln == 0) { mbar_arrive(bars + B_XNE + (j) * 8); mbar_arrive_remote(mapa(bars + B_XNE + (j) * 8, rank ^ 1)); } }

__device__ __forceinline__ void mma_bf16v(float* c, uint32_t a0, uint32_t a1, uint32_t a2, uint32_t a3, uint32_t b0, uint32_t b1) {
  asm volatile("mma.sync.aligned.m16n8k16.row.col.f32.bf16.bf16.f32 {%0,%1,%2,%3}, {%4,%5,%6,%7}, {%8,%9}, {%0,%1,%2,%3};"
      : "+f"(c[0]), "+f"(c[1]), "+f"(c[2]), "+f"(c[3]) : "r"(a0), "r"(a1), "r"(a2), "r"(a3), "r"(b0), "r"(b1));
}
template <int acc>
__device__ __forceinline__ void ss48(float* d, uint64_t a, uint64_t b) {
  asm volatile("wgmma.mma_async.sync.aligned.m64n48k16.f32.bf16.bf16 {%0,%1,%2,%3,%4,%5,%6,%7,%8,%9,%10,%11,%12,%13,%14,%15,%16,%17,%18,%19,%20,%21,%22,%23}, %24, %25, %26, 1, 1, 1, 1;"
    : "+f"(d[0]), "+f"(d[1]), "+f"(d[2]), "+f"(d[3]), "+f"(d[4]), "+f"(d[5]), "+f"(d[6]), "+f"(d[7]), "+f"(d[8]), "+f"(d[9]),
      "+f"(d[10]), "+f"(d[11]), "+f"(d[12]), "+f"(d[13]), "+f"(d[14]), "+f"(d[15]), "+f"(d[16]), "+f"(d[17]), "+f"(d[18]), "+f"(d[19]),
      "+f"(d[20]), "+f"(d[21]), "+f"(d[22]), "+f"(d[23])
    : "l"(a), "l"(b), "n"(acc));
}
template <int TA, int TB>
__device__ __forceinline__ void ssP(uint64_t a, uint64_t b, int sc) {
  asm volatile("{\n.reg .pred p;\nsetp.ne.s32 p, %2, 0;\n"
    "wgmma.mma_async.sync.aligned.m64n32k16.f32.bf16.bf16 {acc0,acc1,acc2,acc3,acc4,acc5,acc6,acc7,acc8,acc9,acc10,acc11,acc12,acc13,acc14,acc15}, %0, %1, p, 1, 1, %3, %4;\n}"
    :: "l"(a), "l"(b), "r"(sc), "n"(TA), "n"(TB));
}
__device__ __forceinline__ void st_async4u(uint32_t addr, uint32_t a, uint32_t b, uint32_t c, uint32_t d, uint32_t bar) {
  asm volatile("st.async.weak.shared::cluster.mbarrier::complete_tx::bytes.v4.b32 [%0], {%1,%2,%3,%4}, [%5];" :: "r"(addr), "r"(a), "r"(b), "r"(c), "r"(d), "r"(bar) : "memory");
}
#define BSYNC(id, n) asm volatile("bar.sync %0, %1;" :: "n"(id), "n"(n) : "memory")
#define BARR(id, n) asm volatile("bar.arrive %0, %1;" :: "n"(id), "n"(n) : "memory")
__device__ __forceinline__ uint32_t max4(const uint4& v) { return max(max(v.x, v.y), max(v.z, v.w)); }
constexpr uint32_t B_TGT = 192;
#define GRID_WAIT() { const uint32_t tg_ = lds1v(bars + B_TGT); int guard = 0; \
          while ((int)(ld_acq1(reinterpret_cast<const uint32_t*>(&g_cnt)) - tg_) < 0) { if (++guard > SPIN_LIMIT) { g_err = 30; break; } } \
          fence_async_all(); }

__device__ __forceinline__ void ld_rlx4p(uint4& v, const uint32_t* p) {
  asm volatile("{\n.reg .pred p;\n.reg .u32 m;\nmax.u32 m, %0, %1;\nmax.u32 m, m, %2;\nmax.u32 m, m, %3;\nsetp.eq.u32 p, m, 0xffffffff;\n"
               "@p ld.relaxed.gpu.global.v4.u32 {%0,%1,%2,%3}, [%4];\n}"
               : "+r"(v.x), "+r"(v.y), "+r"(v.z), "+r"(v.w) : "l"(p) : "memory");
}
__device__ __forceinline__ void ld_rlx1p(uint32_t& v, const uint32_t* p, int pr) {
  asm volatile("{\n.reg .pred q;\nsetp.ne.s32 q, %2, 0;\n@q ld.relaxed.gpu.global.u32 %0, [%1];\n}" : "+r"(v) : "l"(p), "r"(pr) : "memory");
}
#define STG_K 10
#define POLL_MEM(MEMBASE, WGI) { \
          const int q_ = (t & 3) * 4 + 2 * (WGI) + (warp >> 1), sub_ = warp & 1; \
          const uint32_t* gm = g_mem + (h % NCP) * 10240 + q_ * 640 + (sub_ * 32 + ln) * 4; \
          const uint32_t sd = (MEMBASE) + (q_ & 3) * 2560 + (sub_ * 32 + ln) * 16; \
          uint4 v0, v1, v2 = make_uint4(0u, 0u, 0u, 0u); \
          while ((int)(clk32() - gate) < 0) {} \
          int guard = 0; \
          v0 = ld_rlx4(gm); v1 = ld_rlx4(gm + 256); if (!sub_) v2 = ld_rlx4(gm + 512); \
          _Pragma("unroll 1") while (true) { \
            if (!__any_sync(0xffffffffu, max(max(max4(v0), max4(v1)), max4(v2)) == CANARY)) break; \
            if (++guard > SPIN_LIMIT) { g_err = 2; break; } \
            if (PSEL) { ld_rlx4p(v0, gm); ld_rlx4p(v1, gm + 256); ld_rlx4p(v2, gm + 512); } \
            else { v0 = ld_rlx4(gm); v1 = ld_rlx4(gm + 256); if (!sub_) v2 = ld_rlx4(gm + 512); } \
          } \
          sts4(sd, v0.x, v0.y, v0.z, v0.w); sts4(sd + 1024, v1.x, v1.y, v1.z, v1.w); \
          if (!sub_) sts4(sd + 2048, v2.x, v2.y, v2.z, v2.w); }
#define PGAP 250
__device__ __forceinline__ void cp_async16p(uint32_t dst, const void* src, uint32_t pr) {
  asm volatile("{\n.reg .pred q;\nsetp.ne.u32 q, %2, 0;\n@q cp.async.cg.shared.global [%0], [%1], 16;\n}" :: "r"(dst), "l"(src), "r"(pr) : "memory");
}
__device__ __forceinline__ uint32_t ldsmax4(uint32_t addr) {
  uint4 v; asm volatile("ld.volatile.shared.v4.u32 {%0,%1,%2,%3}, [%4];" : "=r"(v.x), "=r"(v.y), "=r"(v.z), "=r"(v.w) : "r"(addr) : "memory");
  return max4(v) == CANARY;
}
#define POLL_MEM2(MEMBASE, WGI, PD) { \
          const int q_ = (t & 3) * 4 + 2 * (WGI) + (warp >> 1), sub_ = warp & 1; \
          const uint32_t* gm = g_mem + (h % NCP) * 10240 + q_ * 640 + (sub_ * 32 + ln) * 4; \
          const uint32_t sd = (MEMBASE) + (q_ & 3) * 2560 + (sub_ * 32 + ln) * 16; \
          uint32_t n0 = 1, n1 = 1, n2 = !sub_; \
          _Pragma("unroll 1") for (int r_ = 0; r_ < (PD); r_++) { \
            while ((int)(clk32() - gate) < 0) {} \
            gate = clk32() + PGAP; \
            cp_async16(sd, gm); cp_async16(sd + 1024, gm + 256); cp_async16p(sd + 2048, gm + 512, n2); cp_async_commit(); } \
          int guard = 0; \
          _Pragma("unroll 1") while (true) { \
            asm volatile("cp.async.wait_group %0;" :: "n"((PD) - 1) : "memory"); \
            n0 = ldsmax4(sd); n1 = ldsmax4(sd + 1024); n2 = ldsmax4(sd + 2048 - sub_ * 1024) & !sub_; \
            if (!__any_sync(0xffffffffu, n0 | n1 | n2)) break; \
            if (++guard > SPIN_LIMIT) { g_err = 2; break; } \
            cp_async16p(sd, gm, n0); cp_async16p(sd + 1024, gm + 256, n1); cp_async16p(sd + 2048, gm + 512, n2); cp_async_commit(); \
          } }
#define EP -1
#define PG2 500
#define MEM_ADDR(MEMBASE, WGI, T) \
          const int q_ = ((T) & 3) * 4 + 2 * (WGI) + (warp >> 1), sub_ = warp & 1; \
          const uint32_t* gm = g_mem + (h % NCP) * 10240 + q_ * 640 + (sub_ * 32 + ln) * 4; (void)gm; \
          const uint32_t sd = (MEMBASE) + (q_ & 3) * 2560 + (sub_ * 32 + ln) * 16
#define MEM_POISON(MEMBASE, WGI) { MEM_ADDR(MEMBASE, WGI, 0); asm volatile("cp.async.wait_all;" ::: "memory"); \
          sts1(sd, CANARY); sts1(sd + 1024, CANARY); sts1(sd + 2048 - sub_ * 1024, CANARY); }
#define MEM_ISSUE(MEMBASE, WGI, T) { MEM_ADDR(MEMBASE, WGI, T); \
          cp_async16(sd, gm); cp_async16(sd + 1024, gm + 256); cp_async16p(sd + 2048, gm + 512, !sub_); gate = clk32() + PG2; }
#define POLL_MEM3(MEMBASE, WGI) { MEM_ADDR(MEMBASE, WGI, t); \
          int guard = 0; \
          _Pragma("unroll 1") while (true) { \
            const uint32_t n0 = ldsmax4(sd), n1 = ldsmax4(sd + 1024), n2 = ldsmax4(sd + 2048 - sub_ * 1024) & !sub_; \
            if (!__any_sync(0xffffffffu, n0 | n1 | n2)) break; \
            if (++guard > SPIN_LIMIT * 8) { g_err = 2; break; } \
            if ((int)(clk32() - gate) >= 0) { \
              cp_async16p(sd, gm, n0); cp_async16p(sd + 1024, gm + 256, n1); cp_async16p(sd + 2048, gm + 512, n2); gate = clk32() + PG2; } \
          } }
#define PDQ 1
#define PDV 1
#define XNE 1
#define FBE 1
#define VFEN 1
#define PSEL 1
#define MOD3(t) ((uint32_t)(t) - 3u * (((uint32_t)(t) * 171u) >> 9))
#define SET_GATE(G) { gate = clk32() + (G); }

#define RS_W(OFF, K0, M, XN) { XLO(sb + (XN)); WG_FENCE(); \
            _Pragma("unroll") for (int ks = (K0); ks < (K0) + (M); ks++) { \
              if (ks == 0) rsA<0, 0>(W[(OFF) + ks], dsc(xl_ + xoff(ks), HI_128)); else rsA<0, 1>(W[(OFF) + ks], dsc(xl_ + xoff(ks), HI_128)); } }

__device__ __forceinline__ uint32_t wgoff_(uint32_t tx_, uint32_t m, uint32_t c) {
  LAUNDER(tx_);
  return __shfl_sync(0xffffffffu, (tx_ >> 7) * m + c, 0);
}
#define wgoff(m) wgoff_(tid, m, 0)
#define TRQ(s) TR((s) + 16 * WG)
#define IDQ() IDS(); const int WG = tx_ >> 7
__device__ __forceinline__ void qk_weights(const uint32_t sb, const uint32_t bars, const uint32_t (&W)[40][4], const uint32_t tid) {
      const int lane = threadIdx.x & 31; (void)lane;
      uint32_t gate = clk32();
      for (int t = -1; t < NSEG; t++) {
        if (t >= 0) {
          IDQ();
          const uint32_t w2a = sb + QK_T2 + WG * 40960 + A_OFF;
          uint32_t a[NPRE][4];
#pragma unroll
          for (int i = 0; i < NPRE; i++) ldsm_x4_t(a[i][0], a[i][1], a[i][2], a[i][3], w2a + i * 2048);
          float e[12];
#pragma unroll
          for (int i = 0; i < 12; i++) e[i] = 0.f;
          const uint32_t baddr = sb + QK_MEM + WG * 5120 + ln * 16;
          const uint32_t R = sb + QK_R + (t & 1) * 6144;
          TRQ(7);
          if (EP >= 0) POLL_MEM3(sb + QK_MEM, WG) else if (PDQ) POLL_MEM2(sb + QK_MEM, WG, PDQ > 0 ? PDQ : 1) else POLL_MEM(sb + QK_MEM, WG);
          bar_sync(1 + WG, 128);
          TRQ(0);
          uint32_t b[2][4];
          ldsm_x4_t(b[0][0], b[0][1], b[0][2], b[0][3], baddr);
#pragma unroll
          for (int kp = 0; kp < 10; kp++) {
            if (kp < 9) ldsm_x4_t(b[(kp + 1) & 1][0], b[(kp + 1) & 1][1], b[(kp + 1) & 1][2], b[(kp + 1) & 1][3], baddr + (kp + 1) * 512);
            const uint32_t* bb = b[kp & 1];
#pragma unroll
            for (int u = 0; u < 2; u++) {
              const int ks = 2 * kp + u;
              uint32_t* aa = a[ks % NPRE];
              mma_bf16(e + 8, aa[0], aa[1], aa[2], aa[3], bb[2 * u], bb[2 * u + 1]);
              if (ks + NPRE < 20) ldsm_x4_t(aa[0], aa[1], aa[2], aa[3], w2a + (ks + NPRE) * 2048);
              mma_bf16(e, W[ks][0], W[ks][1], W[ks][2], W[ks][3], bb[2 * u], bb[2 * u + 1]);
              mma_bf16(e + 4, W[20 + ks][0], W[20 + ks][1], W[20 + ks][2], W[20 + ks][3], bb[2 * u], bb[2 * u + 1]);
            }
          }
          const uint32_t ka = (WG == 0 ? sb + QK_QX + (t & 1) * 12288 + 6144 : R) + ln * 64 + ((warp ^ ((ln >> 1) & 3)) << 4);
          const uint32_t qa = R + (((ln >> 4) << 3) + (ln & 7)) * 64 + (((2 + ((ln >> 3) & 1)) ^ ((ln >> 1) & 3)) << 4);
          const uint32_t sl = sb + QK_S + rank * 1536 + ln * 48 + (WG * 4 + warp) * 8;
          const uint32_t sRa = mapa(sl, rank ^ 1), bRa = mapa(bars + B_S, rank ^ 1);
          {
            const int g = ln >> 2, sw = (g >> 1) & 3;
            const uint32_t rb = R + (warp * 16 + g) * 64 + (ln & 3) * 4;
            const uint32_t cq = ((2 + WG) ^ sw) << 4, ck = (WG ^ sw) << 4;
            const uint32_t r0 = rb + cq, r1 = warp < 2 ? rb + 4096 + cq : rb - 2048 + ck;
            const uint32_t rF = WG ? r0 : r1, rO = WG ? r1 : r0;
            sts1(rb + 2048 + ck, pack_bf16(e[8], e[9]));
            sts1(rb + 2048 + 512 + ck, pack_bf16(e[10], e[11]));
            sts1(rF, pack_bf16(e[0], e[1]));
            sts1(rF + 512, pack_bf16(e[2], e[3]));
            sts1(rO, pack_bf16(e[4], e[5]));
            sts1(rO + 512, pack_bf16(e[6], e[7]));
          }
          TRQ(8);
          BSYNC(3, 384);
          if (t < NSEG - 1 && tx_ < 192) {
            uint32_t kf[12], q[24];
#pragma unroll
            for (int i = 0; i < 3; i++) {
              ldsm_x4_t(kf[4 * i], kf[4 * i + 1], kf[4 * i + 2], kf[4 * i + 3], ka + i * 2048);
              ldsm_x4_t(q[8 * i], q[8 * i + 1], q[8 * i + 2], q[8 * i + 3], qa + (2 * i) * 1024);
              ldsm_x4_t(q[8 * i + 4], q[8 * i + 5], q[8 * i + 6], q[8 * i + 7], qa + (2 * i + 1) * 1024);
            }
#pragma unroll
            for (int i = 0; i < 12; i++) e[i] = 0.f;
#pragma unroll
            for (int ks = 0; ks < 6; ks++)
              mma_bf16(e + (ks % 3) * 4, q[4 * ks], q[4 * ks + 1], q[4 * ks + 2], q[4 * ks + 3], kf[2 * ks], kf[2 * ks + 1]);
            const float s0 = ((e[0] + e[2]) + (e[4] + e[6])) + (e[8] + e[10]);
            const float s1 = ((e[1] + e[3]) + (e[5] + e[7])) + (e[9] + e[11]);
            st_async2(sRa, s0, s1, bRa);
            sts2f(sl, s0, s1);
            WARP_ARRIVE(bars + B_S);
          }
          TRQ(9);
          BSYNC(7, 256);
        }
        if (t + 1 < NSEG) {
          const int seg = t + 1;
          {
            IDQ();
            if (EP >= 0) MEM_POISON(sb + QK_MEM, WG);
            mbar_wait(bars + B_XNF + WG * 8, seg & 1);
          }
          if (N1 > 0) {
            RS_W(0, 0, N1, QK_XN + wgoff(20480));
            WG_COMMIT();
          }
          if (N1 < 20) {
            BSYNC(4, 384);
            SET_GATE(G_Q);
            RS_W(0, N1, 20 - N1, QK_XN + wgoff(20480));
            WG_COMMIT();
          }
          { IDQ(); WAIT_D(); PUT_PART(sb + QK_PB + WG * 8192 + wl * 16); TRQ(11); }
          if (N1 == 20) { BSYNC(4, 384); SET_GATE(G_Q); }
          if (EP > 0 && EP < 20) {
            RS_W(20, 0, EP, QK_XN + wgoff(20480));
            { IDQ(); MEM_ISSUE(sb + QK_MEM, WG, seg); }
            RS_W(20, EP, 20 - EP, QK_XN + wgoff(20480));
          } else {
            if (EP == 0) { IDQ(); MEM_ISSUE(sb + QK_MEM, WG, seg); }
            RS_W(20, 0, 20, QK_XN + wgoff(20480));
          }
          WG_COMMIT();
          if (EP == 20) { IDQ(); MEM_ISSUE(sb + QK_MEM, WG, seg); }
          if (N1 < 20) BSYNC(6, 256);
          {
            IDQ();
            WAIT_D();
            if (NT2 > 0) {
              XLO(sb + QK_XN + wgoff(20480)); const uint32_t wl_ = ((sb + QK_T2 + wgoff(40960)) >> 4) | 0x400000u; WG_FENCE();
#pragma unroll
              for (int j = 0; j < 4 * NT2; j++) {
                if (j == 0) ssA<1, 0, 0>(dsc(wl_, HI_128), dsc(xl_, HI_128));
                else ssA<1, 0, 1>(dsc(wl_ + j * 128, HI_128), dsc(xl_ + (j >> 2) * 256 + (j & 3) * 2, HI_128));
              }
              WG_COMMIT();
            } else XN_RELEASE(WG);
            ADD_PART(sb + QK_PB + (WG ^ 1) * 8192 + wl * 16);
            STORE_T(sb + QK_QX + (seg & 1) * 12288 + WG * 4096);
            TRQ(12);
          }
          if (NT2 > 0) {
            IDQ();
            WAIT_D();
            XN_RELEASE(WG);
            PUT_PART(sb + QK_PB + (WG ^ 1) * 8192 + wl * 16);
            BARR(9, 384);
          }
        } else BARR(11, 384);
      }
}

#define STORE_Z(zz, T) if (t < NSEG - 1) { \
      const int ta_ = (T) * 4 + warp, w_ = (ta_ * 13) >> 6, i_ = ta_ - 5 * w_; \
      uint32_t* zp_ = g_zq + ((t & 3) * 64 + rank * 32 + 8 * w_) * 1280 + (i_ < 4 ? i_ * 2560 + h * 32 + ln : (ln >> 3) * 1280 + 1024 + h * 8 + (ln & 7)); \
      st_rlx1(zp_, pack_bf16(zz[0] + zz[4], zz[1] + zz[5])); \
      st_rlx1(zp_ + (i_ < 4 ? 1280 : 5120), pack_bf16(zz[2] + zz[6], zz[3] + zz[7])); }
#define STORE_B(T) { uint32_t* dst_ = g_B + ((((size_t)((seg - 1) & 1) * 32 + h) * 2 + rank) * 20 + 4 * (T) + warp) * 256 + ln * 4; \
      const uint32_t ph_ = (((seg - 1) >> 1) & 1) ^ 1; \
      WAIT_D(); \
      st_rlx4(dst_, pack_ph(d[0], d[1], ph_), pack_bf16(d[2], d[3]), pack_bf16(d[4], d[5]), pack_bf16(d[6], d[7])); \
      st_rlx4(dst_ + 128, pack_ph(d[8], d[9], ph_), pack_bf16(d[10], d[11]), pack_bf16(d[12], d[13]), pack_bf16(d[14], d[15])); }
#define VLO() uint32_t vl_ = ((sb + VO_VX + ((seg - 1) & 3) * 12288) >> 4) | 0x200000u; LAUNDER(vl_)
#define SPLIT_D(S) float kp[8], gv[8]; \
      _Pragma("unroll") for (int i = 0; i < 4; i++) { \
        kp[2 * i] = (S) ? d[4 * i + 2] : d[4 * i]; kp[2 * i + 1] = (S) ? d[4 * i + 3] : d[4 * i + 1]; \
        gv[2 * i] = (S) ? d[4 * i] : d[4 * i + 2]; gv[2 * i + 1] = (S) ? d[4 * i + 1] : d[4 * i + 3]; }
#define FIN_VX(OFF, S, src, TX) { \
      const float4 o0 = lds4f(src), o1 = lds4f((src) + 2048); \
      const int fo = warp * 16 + (ln >> 2); \
      const uint32_t va = sb + VO_VX + (seg & 3) * 12288 + (OFF) + (S) * 512 + fo * 64 + (((ln & 3) ^ ((fo >> 1) & 3)) << 4); \
      const uint32_t w0 = pack_bf16(kp[0] + o0.x, kp[1] + o0.y), w1 = pack_bf16(kp[2] + o0.z, kp[3] + o0.w); \
      const uint32_t w2 = pack_bf16(kp[4] + o1.x, kp[5] + o1.y), w3 = pack_bf16(kp[6] + o1.z, kp[7] + o1.w); \
      sts4(va, w0, w1, w2, w3); \
      __syncwarp(); \
      if (ln == 0) { if ((TX) && warp == 0) mbar_arrive_tx(bars + B_VXR + (seg & 1) * 8, 6144); else mbar_arrive(bars + B_VXR + (seg & 1) * 8); } \
      st_async4u(mapa(va, rank ^ 1), w0, w1, w2, w3, mapa(bars + B_VXR + (seg & 1) * 8, rank ^ 1)); }

__device__ __forceinline__ void vo_weights(const uint32_t sb, const uint32_t bars, const uint32_t (&W)[40][4], const uint32_t tid) {
      const int lane = threadIdx.x & 31; (void)lane;
      uint32_t gate = clk32();
      for (int t = -2; t < NSEG; t++) {
        const int t_ = t;
        if (ZE ? (t == -2 || t > 0) : t >= 0) {
          const int t = max(t_, 0);
          IDQ();
          const uint32_t ma = sb + VO_MID + WG * 20480 + A_OFF;
          uint32_t a[NPRV][4];
#pragma unroll
          for (int i = 0; i < NPRV; i++) ldsm_x4_t(a[i][0], a[i][1], a[i][2], a[i][3], ma + i * 2048);
          float e[16];
#pragma unroll
          for (int i = 0; i < 12; i++) e[i] = 0.f;
          const uint32_t baddr = sb + VO_MEM + WG * 5120 + (ln ^ (rank << 4)) * 16;
          const uint32_t xs = sb + VO_XM + rank * 4096 + tx_ * 16;
          const uint32_t xR = mapa(xs, rank ^ 1), bR = mapa(bars + B_PC, rank ^ 1);
          TRQ(7);
          if (PDV) POLL_MEM2(sb + VO_MEM, WG, PDV > 0 ? PDV : 1) else POLL_MEM(sb + VO_MEM, WG);
          bar_sync(1 + WG, 128);
          TRQ(0);
          uint32_t b[2][4];
          ldsm_x4_t(b[0][0], b[0][1], b[0][2], b[0][3], baddr);
#pragma unroll
          for (int kp = 0; kp < 10; kp++) {
            if (kp < 9) ldsm_x4_t(b[(kp + 1) & 1][0], b[(kp + 1) & 1][1], b[(kp + 1) & 1][2], b[(kp + 1) & 1][3], baddr + (kp + 1) * 512);
            const uint32_t* bb = b[kp & 1];
            uint32_t* aa = a[kp % NPRV];
            mma_bf16(e + 8, aa[0], aa[1], aa[2], aa[3], bb[0], bb[1]);
            if (kp + NPRV < 10) ldsm_x4_t(aa[0], aa[1], aa[2], aa[3], ma + (kp + NPRV) * 2048);
            mma_bf16(e, W[2 * kp][0], W[2 * kp][1], W[2 * kp][2], W[2 * kp][3], bb[0], bb[1]);
            mma_bf16(e + 4, W[2 * kp + 1][0], W[2 * kp + 1][1], W[2 * kp + 1][2], W[2 * kp + 1][3], bb[2], bb[3]);
          }
          {
            const uint32_t w0 = pack_bf16(e[0] + e[4], e[1] + e[5]), w1 = pack_bf16(e[2] + e[6], e[3] + e[7]);
            const uint32_t w2 = pack_bf16(e[8], e[9]), w3 = pack_bf16(e[10], e[11]);
            st_async4u(xR, w0, w1, w2, w3, bR);
            sts4(xs, w0, w1, w2, w3);
            WARP_ARRIVE(bars + B_PC);
          }
          TRQ(8);
          uint32_t o[16];
          const uint32_t oa = sb + VO_OP + WG * 8192 + A_OFF;
#pragma unroll
          for (int j = 0; j < 4; j++) ldsm_x4_t(o[4 * j], o[4 * j + 1], o[4 * j + 2], o[4 * j + 3], oa + j * 2048);
          const uint32_t vm = sb + VO_VM + MOD3(t) * 3072;
          const uint32_t xr = sb + VO_XM + wl * 16 + WG * 8;
          const uint32_t vd = vm + WG * 1024 + (warp * 16 + (ln >> 2)) * 16 + (ln & 3) * 4;
#pragma unroll
          for (int i = 0; i < 16; i++) e[i] = 0.f;
          mbar_wait(bars + B_PC, t & 1);
          {
            const uint2 x0 = lds2v(xr), x1 = lds2v(xr + 2048), y0 = lds2v(xr + 4096), y1 = lds2v(xr + 6144);
            float4 x = make_float4(bf_lo(x0.x) + bf_lo(x1.x), bf_hi(x0.x) + bf_hi(x1.x), bf_lo(x0.y) + bf_lo(x1.y), bf_hi(x0.y) + bf_hi(x1.y));
            const float4 y = make_float4(bf_lo(y0.x) + bf_lo(y1.x), bf_hi(y0.x) + bf_hi(y1.x), bf_lo(y0.y) + bf_lo(y1.y), bf_hi(y0.y) + bf_hi(y1.y));
            if (WG) { x.x += y.x; x.y += y.y; x.z += y.z; x.w += y.w; }
            else { sts1(vd + 2048, pack_bf16(y.x, y.y)); sts1(vd + 2048 + 128, pack_bf16(y.z, y.w)); }
            sts1(vd, pack_bf16(x.x, x.y));
            sts1(vd + 128, pack_bf16(x.z, x.w));
          }
          TRQ(9);
          BSYNC(3, 384);
#pragma unroll
          for (int kb = 0; kb < 6; kb++) {
            uint32_t b0, b1, b2, b3;
            ldsm_x4_t(b0, b1, b2, b3, vm + ln * 16 + kb * 512);
            mma_bf16(e, W[20 + 2 * kb][0], W[20 + 2 * kb][1], W[20 + 2 * kb][2], W[20 + 2 * kb][3], b0, b1);
            mma_bf16(e + 4, W[21 + 2 * kb][0], W[21 + 2 * kb][1], W[21 + 2 * kb][2], W[21 + 2 * kb][3], b2, b3);
            if (kb < 4) {
              const int k1 = kb < 4 ? 32 + 2 * kb : 0;
              mma_bf16(e + 8, W[k1][0], W[k1][1], W[k1][2], W[k1][3], b0, b1);
              mma_bf16(e + 12, W[k1 + 1][0], W[k1 + 1][1], W[k1 + 1][2], W[k1 + 1][3], b2, b3);
            } else {
              const uint32_t* aa = o + (kb < 4 ? 0 : (kb - 4) * 8);
              mma_bf16(e + 8, aa[0], aa[1], aa[2], aa[3], b0, b1);
              mma_bf16(e + 12, aa[4], aa[5], aa[6], aa[7], b2, b3);
            }
          }
          STORE_Z(e, 2 * WG);
          STORE_Z((e + 8), 2 * WG + 1);
          TRQ(10);
          if (tx_ == 0) mbar_arrive_tx(bars + B_PC, 4096);
        }
        const int seg = t + 2;
        BSYNC(4, 384);
        SET_GATE(G_V);
        if (seg < NSEG) {
          if (seg >= 1) {
            {
              VLO(); WG_FENCE();
#pragma unroll
              for (int ks = 0; ks < 12; ks++) {
                if (ks == 0) rsA<1, 0>(W[20], dsc(vl_, HI_64)); else rsA<1, 1>(W[20 + ks], dsc(vl_ + ks * 64, HI_64));
              }
              WG_COMMIT();
            }
            { IDQ(); STORE_B(2 * WG); }
            {
              VLO(); const uint32_t wl_ = ((sb + VO_OP + wgoff(8192)) >> 4) | 0x400000u; WG_FENCE();
#pragma unroll
              for (int ks = 0; ks < 12; ks++) {
                if (ks == 0) rsA<1, 0>(W[32], dsc(vl_, HI_64));
                else if (ks < 8) rsA<1, 1>(W[ks < 8 ? 32 + ks : 0], dsc(vl_ + ks * 64, HI_64));
                else ssA<1, 1, 1>(dsc(wl_ + (ks - 8) * 128, HI_128), dsc(vl_ + ks * 64, HI_64));
              }
              WG_COMMIT();
            }
            { IDQ(); STORE_B(2 * WG + 1); TRQ(11); }
          }
          {
            IDQ();
            mbar_wait(bars + B_XNF + WG * 8, seg & 1);
          }
          {
            XLO(sb + VO_XN + wgoff_(tid, 20480, (blockIdx.x & 1) * 32));
            const uint32_t xo_ = xl_ ^ 2u;
            WG_FENCE();
#pragma unroll
            for (int j = 0; j < 20; j++) {
              if (j == 0) rsA<0, 0>(W[0], dsc(xl_, HI_128));
              else rsA<0, 1>(W[j], dsc(((j & 1) ? xo_ : xl_) + xoff(j & ~1), HI_128));
            }
            WG_COMMIT();
          }
          {
            IDQ();
            WAIT_D();
            XN_RELEASE(WG);
            SPLIT_D(WG);
            const uint32_t fx = sb + VO_FX + wl * 16;
            sts4f(fx + WG * 4096, gv[0], gv[1], gv[2], gv[3]);
            sts4f(fx + WG * 4096 + 2048, gv[4], gv[5], gv[6], gv[7]);
            BSYNC(5, 256);
            FIN_VX(rank * 8192, WG, fx + (WG ^ 1) * 4096, false);
            TRQ(12);
          }
        }
      }
}

__device__ __forceinline__ void reduce_unit(const int t, const int unit, const int wq, const int ln, const uint32_t bars,
                                            const uint32_t red, const int barid, const uint32_t GP, uint32_t (&z)[10]) {
          const int lane = ln; (void)lane;
          const uint32_t* gp = g_pt + ((t & 3) * 64 + unit) * 1280 + wq * 256 + ln;
          const uint32_t* ge = gp + 1024 - wq * 192;
          uint32_t* md = g_mem + (wq >> 1) * 10240 + ((t + 1) & 3) * 2560 + (unit >> 3) * 320 + ((wq & 1) ? 256 + (unit & 7) * 8 : (unit & 7) * 32) + ln;
          int guard = 0;
          uint32_t w[10], p[8];
          const uint32_t* gz = g_zq + (gp - g_pt);
          const uint32_t* gq = g_pm + (((t & 3) * 2 + (unit & 1)) * 32 + wq * 8) * 32 + ln;
          const uint32_t phase = ((t >> 2) & 1) ? 0u : 0x80008000u;
          while ((int)(clk32() - GP) < 0) {}
          TR(21);
          const uint32_t sp = red + 2048 + wq * 2304 + ln * 4;
#pragma unroll 1
          while (true) {
            uint32_t mx = 0, bad = 0;
            if (PD2 > 0 && (guard & 1)) {
              cp_async_wait0();
              __syncwarp();
#pragma unroll
              for (int i = 0; i < 8; i++) { p[i] = lds1v(sp + i * 128); w[i] = lds1v(sp + 1024 + i * 128); }
              w[8] = lds1v(sp + 2048); w[9] = lds1v(sp + 2176);
            } else {
#pragma unroll
              for (int i = 0; i < 8; i++) p[i] = ld_rlx1(gq + i * 32);
#pragma unroll
              for (int i = 0; i < 8; i++) w[i] = ld_rlx1(gp + i * 32);
              w[8] = ld_rlx1(ge); w[9] = ld_rlx1(ge + 32);
              if (PD2 > 0) {
                const uint32_t c_ = clk32();
                while ((int)(clk32() - c_) < PD2) {}
                cp_async16(sp + ln * 12, gq + ln * 3); cp_async16(sp + ln * 12 + 512, gq + ln * 3 + 128);
                cp_async16(sp + ln * 12 + 1024, gp + ln * 3); cp_async16(sp + ln * 12 + 1536, gp + ln * 3 + 128);
                cp_async16p(sp + ln * 12 + 2048, ge + ln * 3, ln < 16);
                cp_async_commit();
              }
            }
#pragma unroll
            for (int i = 0; i < 8; i++) bad |= p[i] ^ phase;
#pragma unroll
            for (int i = 0; i < 10; i++) mx = max(mx, w[i]);
            if (!__any_sync(0xffffffffu, mx == CANARY || (bad & 0x80008000u) != 0)) break;
            if (++guard > SPIN_LIMIT) { g_err = 4; break; }
          }
          TR(19);
#pragma unroll 1
          while (true) {
            uint32_t mx = 0;
#pragma unroll
            for (int i = 0; i < 10; i++) mx = max(mx, z[i]);
            if (!__any_sync(0xffffffffu, mx == CANARY)) break;
            if (++guard > SPIN_LIMIT) { g_err = 7; break; }
#pragma unroll
            for (int i = 0; i < 8; i++) z[i] = ld_rlx1(gz + i * 32);
            z[8] = ld_rlx1(gz + 1024 - wq * 192); z[9] = ld_rlx1(gz + 1056 - wq * 192);
          }
          float d[4][4];
#pragma unroll
          for (int j = 0; j < 4; j++) {
            d[j][0] = bf_lo(w[2 * j]) + bf_lo(w[2 * j + 1]); d[j][1] = bf_hi(w[2 * j]) + bf_hi(w[2 * j + 1]);
            d[j][2] = j < 2 ? bf_lo(w[8 + (j & 1)]) : 0.f; d[j][3] = j < 2 ? bf_hi(w[8 + (j & 1)]) : 0.f;
            mma_bf16(d[j], z[2 * j], (ln >> 3) == ((2 * j) & 3) ? z[8 + (j >> 1)] : 0u, z[2 * j + 1], (ln >> 3) == ((2 * j + 1) & 3) ? z[8 + (j >> 1)] : 0u,
                     p[2 * j] & 0x7fff7fffu, p[2 * j + 1] & 0x7fff7fffu);
          }
          float el = (d[0][2] + d[1][2]) + (d[2][2] + d[3][2]), eh = (d[0][3] + d[1][3]) + (d[2][3] + d[3][3]);
          el += __shfl_xor_sync(0xffffffffu, el, 8); eh += __shfl_xor_sync(0xffffffffu, eh, 8);
          const float lo = (d[0][0] + d[1][0]) + (d[2][0] + d[3][0]), hi = (d[0][1] + d[1][1]) + (d[2][1] + d[3][1]);
          sts2f(red + wq * 256 + ln * 8, lo, hi);
          el += __shfl_xor_sync(0xffffffffu, el, 16); eh += __shfl_xor_sync(0xffffffffu, eh, 16);
          sts2f(red + 1024 + wq * 256 + ln * 8, el, eh);
          TR(22);
          bar_sync(barid, 128);
          if (NCP > 1 || wq < 2) {
            const uint32_t rr = red + (wq & 1) * 1024 + ln * 8;
            const float2 a0 = lds2f(rr), a1 = lds2f(rr + 256), a2 = lds2f(rr + 512), a3 = lds2f(rr + 768);
            const uint32_t r_ = pack_bf16((a0.x + a2.x) + (a1.x + a3.x), (a0.y + a2.y) + (a1.y + a3.y));
            if (!(wq & 1) || ln < 8) {
#pragma unroll
              for (int c = 0; c < (NCP + 1) / 2; c++) st_rlx1(md + c * 20480, r_);
            }
          }
          TR(6);
}
__device__ __forceinline__ void resets(const int tp, const int unit, const int wq, const int ln) {
          uint32_t* gp = g_pt + ((tp & 3) * 64 + unit) * 1280 + (wq * 32 + ln) * 4;
          st_rlx4(gp, CANARY, CANARY, CANARY, CANARY);
          st_rlx4(gp + 512, CANARY, CANARY, CANARY, CANARY);
          uint32_t* gz = g_zq + (gp - g_pt);
          st_rlx4(gz, CANARY, CANARY, CANARY, CANARY);
          st_rlx4(gz + 512, CANARY, CANARY, CANARY, CANARY);
          if (wq < 2) { st_rlx4(gp + 1024, CANARY, CANARY, CANARY, CANARY); st_rlx4(gz + 1024, CANARY, CANARY, CANARY, CANARY); }
          else if (wq == 2 || ln < 8) {
#pragma unroll
            for (int c = 0; c < NCP; c++)
              st_rlx1(g_mem + c * 10240 + ((tp + 3) & 3) * 2560 + (unit >> 3) * 320 + (wq == 3 ? 256 + (unit & 7) * 8 : (unit & 7) * 32) + ln, CANARY);
          }
}
#define XN_ISSUE1(XN, seg_, j) { \
              if ((seg_) > 0) mbar_wait(bars + B_XNE + (j) * 8, ((seg_) - 1) & 1); \
              mbar_arrive_tx(bars + B_XNF + (j) * 8, 20480); \
              bulk_g2s_mc(sb + (XN) + (j) * 20480 + rank * 10240, reinterpret_cast<const uint8_t*>(g_xnT) + (size_t)(seg_) * 40960 + (j) * 20480 + rank * 10240, \
                          10240, bars + B_XNF + (j) * 8, 3); }
#define FETCH_B(seg_) { \
          const uint32_t* src = g_B + ((((size_t)((seg_) & 1) * 32 + h) * 2 + rank) * 20 + warp * 5) * 256 + ln * 4; \
          _Pragma("unroll") for (int i = 0; i < 10; i++) cp_async16(sb + QK_BS + warp * 5120 + i * 512 + ln * 16, src + i * 128); \
          cp_async_commit(); }
__device__ __forceinline__ void tma2o(uint32_t dst, const CUtensorMap* tm, int c0, int c1, uint32_t bar) {
  if (HINT & 8) asm volatile("cp.async.bulk.tensor.2d.shared::cluster.global.mbarrier::complete_tx::bytes.L2::cache_hint [%0], [%1, {%2,%3}], [%4], %5;"
               :: "r"(dst), "l"(tm), "r"(c0), "r"(c1), "r"(bar), "l"(pol_first()) : "memory");
  else asm volatile("cp.async.bulk.tensor.2d.shared::cluster.global.mbarrier::complete_tx::bytes [%0], [%1, {%2,%3}], [%4];"
               :: "r"(dst), "l"(tm), "r"(c0), "r"(c1), "r"(bar) : "memory");
}
__device__ __forceinline__ void tma2(uint32_t dst, const CUtensorMap* tm, int c0, int c1, uint32_t bar) {
  if (HINT & 1) asm volatile("cp.async.bulk.tensor.2d.shared::cluster.global.mbarrier::complete_tx::bytes.L2::cache_hint [%0], [%1, {%2,%3}], [%4], %5;"
               :: "r"(dst), "l"(tm), "r"(c0), "r"(c1), "r"(bar), "l"(pol_first()) : "memory");
  else
  asm volatile("cp.async.bulk.tensor.2d.shared::cluster.global.mbarrier::complete_tx::bytes [%0], [%1, {%2,%3}], [%4];"
               :: "r"(dst), "l"(tm), "r"(c0), "r"(c1), "r"(bar) : "memory");
}
__device__ __forceinline__ void tma2_pf(const CUtensorMap* tm, int c0, int c1) {
  asm volatile("cp.async.bulk.prefetch.tensor.2d.L2.global [%0, {%1,%2}];" :: "l"(tm), "r"(c0), "r"(c1) : "memory");
}
struct WMaps { CUtensorMap q64, k64, v64, o64, v16, q32, k32, w1; };
constexpr uint32_t ST_A = 81920, ST_B = 163840, ST_L = 122880, B_WA = 200, B_WB = 208;

__global__ void __cluster_dims__(2, 1, 1) __launch_bounds__(384, 1) chain_kernel(const __grid_constant__ WMaps M, ChainParams P) {
  extern __shared__ __align__(1024) uint8_t smem_raw[];
  const uint32_t sb = smem_u32(smem_raw);
  const uint32_t bars = sb + BARS;
  asm volatile(".reg .f32 acc<16>;");
  const int tid = threadIdx.x, wt = tid & 127, lane = tid & 31;
  const int wg = __shfl_sync(0xffffffffu, tid >> 7, 0), warp = wt >> 5;
  const int type = blockIdx.x >= 128 ? 2 : (blockIdx.x >> 1) & 1;
  if (tid == 0 && (sb & 1023u)) g_err = 99;
#define a_off ((uint32_t)(((lane & 7) + ((lane >> 4) & 1) * 8) * 128 + (((2 * warp + ((lane >> 3) & 1)) ^ (lane & 7)) << 4)))
  if (tid == 0) TLM(0);
  {
    ROLE_IDS();
    if (type == 2) {
      if (tid == 0) {
        for (int i = 0; i < 8; i++) { mbar_init(sb + 8 * 24576 + i * 8, 1); mbar_init(sb + 8 * 24576 + 64 + i * 8, 16); }
        asm volatile("fence.mbarrier_init.release.cluster;" ::: "memory");
      }
      const int gt = (bx_ - 128) * 384 + tid;
#pragma unroll 1
      for (int o = gt; o < 4 * 2560; o += 4 * 384) {
        uint32_t w = CANARY;
        if (o < 2560) {
          const unsigned short* m = reinterpret_cast<const unsigned short*>(P.mem0) + (o & 3) * 1280 + (o >> 2);
          w = (uint32_t)m[0] | ((uint32_t)m[640] << 16);
          if ((w & 0xffffu) == 0xffffu) w = (w & 0xffff0000u) | 0x7fffu;
        }
        for (int c = 0; c < NCP; c++) g_mem[c * 10240 + o] = w;
      }
      if (gt < 32) g_flag[gt] = 0;
      cluster_sync();
    } else {
      if (wg == 2) {
        if (wt == 0) {
          mbar_init(bars + B_WA, 1); mbar_init(bars + B_WB, 2);
          fence_async_smem();
          mbar_arrive_tx(bars + B_WA, 81920);
          mbar_arrive_tx(bars + B_WB, 147456);
          if (type == 0) {
            const int c0 = h * DH_ + 96 * rank;
#pragma unroll 1
            for (int j = 0; j < 5; j++) {
              tma2(sb + ST_A + j * 8192, &M.q32, c0 + 64, j * 64, bars + B_WA);
              tma2(sb + ST_A + j * 8192 + 4096, &M.k32, c0, j * 64, bars + B_WA);
              tma2(sb + ST_A + 40960 + j * 8192, &M.q64, c0, 320 + j * 64, bars + B_WA);
            }
#pragma unroll 1
            for (int j = 0; j < 4; j++) {
              tma2(sb + ST_B + j * 8192, &M.q64, c0, j * 64, bars + B_WB);
              tma2(sb + ST_B + 32768 + j * 8192, &M.q32, c0 + 64, 320 + j * 64, bars + B_WB);
              tma2(sb + ST_B + 32768 + j * 8192 + 4096, &M.k32, c0, 320 + j * 64, bars + B_WB);
            }
#pragma unroll 1
            for (int j = 0; j < 10; j++) tma2(sb + QK_T2 + j * 8192, &M.k64, c0 + 32, j * 64, bars + B_WB);
            mbar_init(bars + B_S, 7);
            for (int i = 0; i < 2; i++) { mbar_init(bars + B_XNF + i * 8, 1); mbar_init(bars + B_XNE + i * 8, 16); mbar_init(bars + B_X + i * 8, 1); }
            mbar_arrive_tx(bars + B_S, 1536);
          } else {
            const int c0 = 320 * rank, r0 = h * DH_;
#pragma unroll 1
            for (int j = 0; j < 10; j++) tma2(sb + ST_A + j * 8192, &M.v64, r0 + rank * 128, j * 64, bars + B_WA);
#pragma unroll 1
            for (int j = 0; j < 20; j++) tma2(sb + VO_MID + j * 2048, &M.v16, r0 + 64, j * 32 + rank * 16, bars + B_WB);
#pragma unroll 1
            for (int j = 0; j < 3; j++) {
              tma2o(sb + ST_B + j * 8192, &M.o64, c0, r0 + j * 64, bars + B_WB);
              tma2o(sb + ST_B + 32768 + j * 8192, &M.o64, c0 + 128, r0 + j * 64, bars + B_WB);
              tma2o(sb + VO_O4 + j * 8192, &M.o64, c0 + 256, r0 + j * 64, bars + B_WB);
            }
#pragma unroll 1
            for (int w = 0; w < 2; w++) {
              tma2o(sb + ST_B + w * 32768 + 24576, &M.o64, c0 + 128 * w + 64, r0, bars + B_WB);
              tma2o(sb + VO_OP + w * 8192, &M.o64, c0 + 128 * w + 64, r0 + 128, bars + B_WB);
            }
            mbar_init(bars + B_PC, 9);
            for (int i = 0; i < 2; i++) {
              mbar_init(bars + B_XNF + i * 8, 1); mbar_init(bars + B_XNE + i * 8, 16); mbar_init(bars + B_PB + i * 8, 1);
              mbar_init(bars + B_VXR + i * 8, 12);
            }
            mbar_arrive_tx(bars + B_PC, 4096);
          }
          asm volatile("fence.mbarrier_init.release.cluster;" ::: "memory");
        }
        __syncwarp();
        const int gt = bx_ * 128 + wt;
        const uint4 cn = make_uint4(CANARY, CANARY, CANARY, CANARY), zr = make_uint4(0u, 0u, 0u, 0u);
#pragma unroll 1
        for (int i = gt; i < 4 * 64 * 320; i += 128 * 128) {
          reinterpret_cast<uint4*>(g_zq)[i] = cn;
          reinterpret_cast<uint4*>(g_pt)[i] = cn;
          g_B4[i] = zr;
          g_B4[i + 4 * 64 * 320] = zr;
          if (i < 4 * 4 * 32 * 40) g_p4[i] = zr;
          if (i < 2048) reinterpret_cast<uint4*>(g_pm)[i] = zr;
        }
      } else {
        uint32_t xw[2][10];
        const int row = bx_ * 16 + (tid >> 6) * 4 + ((tid >> 5) & 1);
        const uint32_t* xr = reinterpret_cast<const uint32_t*>(P.x + (size_t)row * D_) + lane;
#pragma unroll
        for (int i = 0; i < 20; i++) xw[i / 10][i % 10] = __ldg(xr + (i / 10) * 640 + (i % 10) * 32);
        ln_rows(xw[0], xw[1], row, lane);
        if (tid == 0) TLM(12);

      }
      __syncthreads();
    }
    if (tid == 0) {
      __threadfence();
      const unsigned long long old = atomicAdd(&g_cnt, 1ull);
      sts1(bars + B_TGT, (uint32_t)((old / 132 + 1) * 132));
      TLM(1);
    }
  }
  if (type == 0) {
    if (wg < 2) {
      asm volatile("setmaxnreg.inc.sync.aligned.u32 208;");
      uint32_t W[40][4];
      {
        const uint32_t r_ = (lane & 7) + ((lane >> 4) & 1) * 8;
        const uint32_t o1 = (warp >> 1) * 4096 + r_ * 64 + (((2 * (warp & 1) + ((lane >> 3) & 1)) ^ ((r_ >> 1) & 3)) << 4);
        const uint32_t bA = sb + ST_A + wg * 40960 + (wg ? a_off : o1), mA = wg ? 2048 : 1024;
        const uint32_t bB = (wg ? o1 : a_off), mB = wg ? 1024 : 2048;
        mbar_wait(bars + B_WA, 0);
        if (tid == 0) TLM(4);
#pragma unroll
        for (int ks = 0; ks < 20; ks++) ldsm_x4_t(W[ks][0], W[ks][1], W[ks][2], W[ks][3], bA + (ks >> 2) * 8192 + (ks & 3) * mA);
        cluster_sync();
        mbar_wait(bars + B_WB, 0);
#pragma unroll
        for (int ks = 0; ks < 20; ks++)
          ldsm_x4_t(W[20 + ks][0], W[20 + ks][1], W[20 + ks][2], W[20 + ks][3],
                    sb + bB + (ks < 16 ? ST_B + wg * 32768 + (ks >> 2) * 8192 : ST_L + wg * 8192) + (ks & 3) * mB);
        cluster_sync();
      }
      if (tid == 0) TLM(5);
      qk_weights(sb, bars, W, tid);
    } else {
      asm volatile("setmaxnreg.dec.sync.aligned.u32 88;");
      cluster_sync();
      {
        IDS();
        if (ln == 0 && warp < 2) { GRID_WAIT(); XN_ISSUE1(QK_XN, 0, warp); }
        if (wl == 64) {
          const int c0 = h * DH_ + 96 * rank;
          mbar_arrive_tx(bars + B_WB, 16384);
          tma2(sb + ST_L, &M.q64, c0, 256, bars + B_WB);
          tma2(sb + ST_L + 8192, &M.q32, c0 + 64, 576, bars + B_WB);
          tma2(sb + ST_L + 8192 + 4096, &M.k32, c0, 576, bars + B_WB);
        }
        __syncwarp();
      }
      mbar_wait(bars + B_WB, 0);
      cluster_sync();
      for (int t = -1; t < NSEG; t++) {
        if (t == TPDL) asm volatile("griddepcontrol.launch_dependents;");
        if (t >= 0 && t < NSEG - 1) {
          IDS();
          const uint32_t sa = sb + QK_S + ln * 48, ba = sb + QK_BS + warp * 5120 + ln * 16;
          {
            const uint32_t ph_ = ((t >> 1) & 1) ^ 1;
            int guard = 0;
#pragma unroll 1
            while (true) {
              cp_async_wait0();
              uint32_t bad = 0;
#pragma unroll
              for (int i = 0; i < 10; i++) bad |= lds1v(ba + i * 512) ^ ph_;
              if (!__any_sync(0xffffffffu, bad & 1)) break;
              if (++guard > SPIN_LIMIT) { g_err = 8; break; }
              FETCH_B(t);
            }
          }
          uint32_t* d0 = g_pt + ((t & 3) * 64 + rank * 32 + 8 * warp) * 1280 + h * 32 + ln;
          uint32_t* d1 = g_pt + ((t & 3) * 64 + rank * 32 + 8 * warp + (ln >> 3)) * 1280 + 1024 + h * 8 + (ln & 7);
          uint32_t* gq = g_pm + (((t & 3) * 2 + rank) * 32 + h) * 32 + ln;
          uint4 Bf[10];
#pragma unroll
          for (int i = 0; i < 6; i++) Bf[i] = lds4(ba + i * 512);
          TR(14);
          mbar_wait(bars + B_S, t & 1);
          TR(1);
          float s[10];
          {
            const float4 x0 = lds4f(sa), y0 = lds4f(sa + 1536), x1 = lds4f(sa + 16), y1 = lds4f(sa + 1552), x2 = lds4f(sa + 32), y2 = lds4f(sa + 1568);
            s[0] = x0.x + y0.x; s[1] = x0.y + y0.y; s[2] = x0.z + y0.z; s[3] = x0.w + y0.w;
            s[4] = x1.x + y1.x; s[5] = x1.y + y1.y; s[6] = x1.z + y1.z; s[7] = x1.w + y1.w;
            s[8] = (x2.x + y2.x) + (x2.z + y2.z); s[9] = (x2.y + y2.y) + (x2.w + y2.w);
          }
          float m = fmaxf(fmaxf(fmaxf(s[0], s[1]), fmaxf(s[2], s[3])), fmaxf(fmaxf(fmaxf(s[4], s[5]), fmaxf(s[6], s[7])), fmaxf(s[8], s[9])));
          m = fmaxf(m, __shfl_xor_sync(0xffffffffu, m, 1));
          m = fmaxf(m, __shfl_xor_sync(0xffffffffu, m, 2));
          constexpr float C = SCALE * 1.4426950408889634f;
          const float mc = -m * C;
#pragma unroll
          for (int j = 0; j < 10; j++) s[j] = ex2f(fmaf(s[j], C, mc));
          const uint32_t p0 = pack_bf16(s[0], s[1]), p1 = pack_bf16(s[2], s[3]), p2 = pack_bf16(s[4], s[5]), p3 = pack_bf16(s[6], s[7]);
          float sum = ((s[0] + s[1]) + (s[2] + s[3])) + (((s[4] + s[5]) + (s[6] + s[7])) + (s[8] + s[9]));
#pragma unroll
          for (int i = 6; i < 10; i++) Bf[i] = lds4(ba + i * 512);
          sum += __shfl_xor_sync(0xffffffffu, sum, 1);
          sum += __shfl_xor_sync(0xffffffffu, sum, 2);
          const float ig = rcpf(sum);
          if (warp == PMW) st_rlx1(gq, pack_bf16(s[8] * ig, s[9] * ig) | (((t >> 2) & 1) ? 0u : 0x80008000u));
          const float i0 = __shfl_sync(0xffffffffu, ig, (ln & 3) * 8), i1 = __shfl_sync(0xffffffffu, ig, (ln & 3) * 8 + 4);
          TR(4);
          float e[20];
#pragma unroll
          for (int i = 0; i < 20; i++) e[i] = 0.f;
#pragma unroll
          for (int i = 0; i < 5; i++) mma_bf16v(e + 4 * i, Bf[2 * i].x, Bf[2 * i].y, Bf[2 * i].z, Bf[2 * i].w, p0, p1);
#pragma unroll
          for (int i = 0; i < 5; i++) mma_bf16v(e + 4 * i, Bf[2 * i + 1].x, Bf[2 * i + 1].y, Bf[2 * i + 1].z, Bf[2 * i + 1].w, p2, p3);
          TR(5);
#pragma unroll
          for (int i = 0; i < 10; i++)
            st_rlx1(i < 8 ? d0 + i * 1280 : d1 + (i - 8) * 4 * 1280, pack_bf16(e[2 * i] * i0, e[2 * i + 1] * i1));
          if (!NB4) BARR(4, 384);
          TR(2);
        } else if (t < 0) BARR(4, 384);
        else BSYNC(11, 384);
#define KX(K0, K1) if (t + 1 < NSEG) {     \
          if ((K0) == 0) { mbar_wait(bars + B_XNF, (t + 1) & 1); mbar_wait(bars + B_XNF + 8, (t + 1) & 1); } \
          XLO(sb + QK_XN); uint32_t wl_ = ((sb + QK_T2) >> 4) | 0x400000u; LAUNDER(wl_); \
          _Pragma("unroll 1") for (int j = (K0); j < (K1); j++) { \
            const int kb = j + (j < 5 - NT2 ? NT2 : 2 * NT2); \
            WG_FENCE(); \
            ssP<1, 0>(dsc(wl_ + kb * 512, HI_128), dsc(xl_ + kb * 256, HI_128), j); \
            _Pragma("unroll") for (int u = 1; u < 4; u++) ssA<1, 0, 1>(dsc(wl_ + kb * 512 + u * 128, HI_128), dsc(xl_ + kb * 256 + u * 2, HI_128)); \
            WG_COMMIT(); \
          } \
        }
        const uint32_t cq = clk32();
        if (NW1 > 0) KX(0, NW1);
        if (NB4 && t >= 0 && t < NSEG - 1) BARR(4, 384);
        if (t >= 0 && t < NSEG - 1) {
          IDS();
          uint32_t z[10];
          TR(20);
          if (FP) fence_async_smem();
          const uint32_t* gz = g_zq + ((t & 3) * 64 + 2 * h + rank) * 1280 + warp * 256 + ln;
          while ((int)(clk32() - (cq + GATE_Z)) < 0) {}
#pragma unroll
          for (int i = 0; i < 8; i++) z[i] = ld_rlx1(gz + i * 32);
          z[8] = ld_rlx1(gz + 1024 - warp * 192); z[9] = ld_rlx1(gz + 1056 - warp * 192);
          reduce_unit(t, 2 * h + rank, warp, ln, bars, sb + QK_RED, 8, cq + GATE_PV, z);
          if (wl == 0 && t == 0) TLM(6);
        }
        if (NW1 < 10 - 2 * NT2) KX(NW1, 10 - 2 * NT2);
        float sc[24];
#pragma unroll
        for (int i = 0; i < 24; i++) sc[i] = 0.f;
        {
          const uint32_t qx = sb + QK_QX + (t & 1) * 12288;
          const uint64_t ad = mkdesc(qx, 0, 512, 2), bd = mkdesc(qx + 6144, sb + QK_R + (t & 1) * 6144 - (qx + 6144), 512, 2);
          if (wt == 0 && t >= 0) mbar_arrive_tx(bars + B_X + (t & 1) * 8, 2560);
          if (!FP || t < 0 || t == NSEG - 1) fence_async_smem();
          WG_FENCE();
          ss48<0>(sc, ad, bd);
#pragma unroll
          for (int ks = 1; ks < 6; ks++) ss48<1>(sc, ad + ks * 64, bd + ks * 64);
          WG_COMMIT();
          WG_WAIT1();
          if (t + 1 < NSEG) {
            IDS();
            GET_D();
            XN_RELEASE(0); XN_RELEASE(1);
            if (NT2 > 0) { BSYNC(9, 384); ADD_PART(sb + QK_PB + wl * 16); ADD_PART(sb + QK_PB + 8192 + wl * 16); }
            STORE_T(sb + QK_QX + ((t + 1) & 1) * 12288 + 8192);
            if (wl == 0 && t >= 0) mbar_arrive_tx(bars + B_S, 1536);
            BARR(3, 384);
            if (t + 2 < NSEG) FETCH_B(t + 1);
            TR(10);
          }
          WG_WAIT0();
        }
        {
          IDS();
          const int hi = warp >> 1;
          const uint32_t xa = sb + QK_SCX + (t & 1) * 2560 + hi * 1280 + ln * 8;
          float s[5][2];
#pragma unroll
          for (int j = 0; j < 4; j++) { s[j][0] = hi ? sc[4 * j + 2] : sc[4 * j]; s[j][1] = hi ? sc[4 * j + 3] : sc[4 * j + 1]; }
          s[4][0] = hi ? sc[18] + sc[22] : sc[16] + sc[20]; s[4][1] = hi ? sc[19] + sc[23] : sc[17] + sc[21];
          if ((warp & 1) != rank && t >= 0) {
            const uint32_t dst = mapa(xa, rank ^ 1), bx = mapa(bars + B_X + (t & 1) * 8, rank ^ 1);
#pragma unroll
            for (int j = 0; j < 5; j++) st_async2(dst + j * 256, s[j][0], s[j][1], bx);
          }
          if (!W1S && t + 1 < NSEG) {
            GET_D();
            XN_RELEASE(0); XN_RELEASE(1);
            if (NT2 > 0) { BSYNC(9, 384); ADD_PART(sb + QK_PB + wl * 16); ADD_PART(sb + QK_PB + 8192 + wl * 16); }
            STORE_T(sb + QK_QX + ((t + 1) & 1) * 12288 + 8192);
            if (wl == 0 && t >= 0) mbar_arrive_tx(bars + B_S, 1536);
            BARR(3, 384);
            if (t + 2 < NSEG) FETCH_B(t + 1);
            TR(10);
          }
          if ((warp & 1) != rank) {
            if (ln == 0 && t + 2 < NSEG) XN_ISSUE1(QK_XN, t + 2, warp >> 1);
          } else if (t >= 0) {
            const uint32_t phase = ((t >> 2) & 1) ? 0u : 0x80008000u;
            uint32_t* pd4 = g_p + ((size_t)((t & 3) * 4 + 2 * rank + hi) * 32 + h) * 160 + ln * 4;
            const int qrow = 8 * (ln >> 3) + 4 * rank + ((ln >> 2) & 1) + 2 * hi;
            mbar_wait(bars + B_X + (t & 1) * 8, (t >> 1) & 1);
#pragma unroll
            for (int j = 0; j < 5; j++) {
              const float2 v = lds2f(xa + j * 256);
              scale_pair(s[j][0] + v.x, s[j][1] + v.y, s[j][0], s[j][1]);
              if (j < 4) {
                const int k0 = 8 * (ln & 3) + 2 * j;
                if (k0 > qrow) s[j][0] = -1e9f;
                if (k0 + 1 > qrow) s[j][1] = -1e9f;
              }
            }
            uint32_t w[5];
            softmax_row(s, w);
            st_rlx4(pd4, w[0] | phase, w[1] | phase, w[2] | phase, w[3] | phase);
            st_rlx1(pd4 + 128 - ln * 3, w[4] | phase);
          }
          __syncwarp();
          if (t >= 0 && t + 2 < NSEG) resets(t, 2 * h + rank, warp, ln);
          TR(3);
        }
      }
    }
  } else if (type == 1) {
    if (wg < 2) {
      asm volatile("setmaxnreg.inc.sync.aligned.u32 216;");
      uint32_t W[40][4];
      {
        const uint32_t r2 = (blockIdx.x & 1) * 2048;
        mbar_wait(bars + B_WA, 0);
#pragma unroll
        for (int j = 0; j < 20; j++) ldsm_x4_t(W[j][0], W[j][1], W[j][2], W[j][3], sb + ST_A + wg * 40960 + a_off + ((j * 2048) ^ r2));
        cluster_sync();
        mbar_wait(bars + B_WB, 0);
#pragma unroll
        for (int j = 0; j < 20; j++)
          ldsm_x4_t(W[20 + j][0], W[20 + j][1], W[20 + j][2], W[20 + j][3], sb + a_off + (j < 16 ? ST_B + wg * 32768 + j * 2048 : ST_L + wg * 8192 + (j - 16) * 2048));
        cluster_sync();
      }
      vo_weights(sb, bars, W, tid);
    } else {
      asm volatile("setmaxnreg.dec.sync.aligned.u32 72;");
      cluster_sync();
      {
        IDS();
        if (ln == 0 && warp < 2) { GRID_WAIT(); XN_ISSUE1(VO_XN, 0, warp); }
        if (wl == 64) {
          mbar_arrive_tx(bars + B_WB, 16384);
          tma2o(sb + ST_L, &M.o64, 320 * rank + 64, h * DH_ + 64, bars + B_WB);
          tma2o(sb + ST_L + 8192, &M.o64, 320 * rank + 192, h * DH_ + 64, bars + B_WB);
        }
        __syncwarp();
      }
      mbar_wait(bars + B_WB, 0);
      cluster_sync();
      if (wt < 32) sts4(sb + VO_PX + (wt >> 3) * 768 + 640 + (wt & 7) * 16, 0u, 0u, 0u, 0u);
      for (int t = -2; t <= NSEG; t++) {
        if (wt == 0 && t <= 0) TLM(15 + t);
        if (t == TPDL) asm volatile("griddepcontrol.launch_dependents;");
        uint32_t cvm = clk32() - GATE_PV;
        const int t_ = t;
        if (ZE ? (t == -2 || (t > 0 && t < NSEG)) : (t >= 0 && t < NSEG)) {
          const int t = max(t_, 0);
          IDS();
          const uint32_t vm_a = sb + VO_VM + MOD3(t) * 3072 + ln * 16, oa = sb + VO_O4 + A_OFF;
          uint32_t a[40];
#pragma unroll
          for (int j = 0; j < 10; j++) ldsm_x4_t(a[4 * j], a[4 * j + 1], a[4 * j + 2], a[4 * j + 3], oa + j * 2048);
          float z[8];
#pragma unroll
          for (int i = 0; i < 8; i++) z[i] = 0.f;
          BSYNC(3, 384);
          cvm = clk32();
          TR(1);
#pragma unroll
          for (int kb = 0; kb < 6; kb++) {
            uint32_t b0, b1, b2, b3;
            ldsm_x4_t(b0, b1, b2, b3, vm_a + kb * 512);
            const uint32_t* aa = a + (kb % 5) * 8;
            mma_bf16(z, aa[0], aa[1], aa[2], aa[3], b0, b1);
            mma_bf16(z + 4, aa[4], aa[5], aa[6], aa[7], b2, b3);
            if (kb == 0) {
              ldsm_x4_t(a[0], a[1], a[2], a[3], oa + 10 * 2048);
              ldsm_x4_t(a[4], a[5], a[6], a[7], oa + 11 * 2048);
            }
          }
          STORE_Z(z, 4);
          TR(2);
        }
        const int seg = t + 2;
        uint4 px = make_uint4(0u, 0u, 0u, 0u); uint32_t pm = 0u;
        const uint32_t* psrc;
        {
          IDS();
          psrc = g_p + ((size_t)(((t - 1) & 3) * 4 + warp) * 32 + h) * 160 + ln;
          if (t >= 1) { px = ld_rlx4(psrc + ln * 3); pm = ld_rlx1(psrc + 128); }
        }
        if (t < NSEG) BSYNC(4, 384);
#define MIDV(K0, K1) if (seg < NSEG) {     \
          if ((K0) == 0) { mbar_wait(bars + B_XNF, seg & 1); mbar_wait(bars + B_XNF + 8, seg & 1); } \
          XLO(sb + VO_XN + (blockIdx.x & 1) * 32); uint32_t wl_ = ((sb + VO_MID) >> 4) | 0x400000u; LAUNDER(wl_); \
          _Pragma("unroll 1") for (int kb = (K0); kb < (K1); kb++) { \
            WG_FENCE(); \
            ssP<1, 0>(dsc(wl_ + kb * 512, HI_128), dsc(xl_ + kb * 512, HI_128), kb); \
            _Pragma("unroll") for (int u = 1; u < 4; u++) ssA<1, 0, 1>(dsc(wl_ + kb * 512 + u * 128, HI_128), dsc(xl_ + kb * 512 + (u >> 1) * 256 + (u & 1) * 4, HI_128)); \
            WG_COMMIT(); \
          } \
        }
        MIDV(0, 5);
        if (t >= 1) {
          IDS();
          const uint32_t phase = (((t - 1) >> 2) & 1) ? 0u : 0x80008000u;
          int guard = 0;
#pragma unroll 1
          while (true) {
            const uint32_t bad = (px.x ^ phase) | (px.y ^ phase) | (px.z ^ phase) | (px.w ^ phase) | (pm ^ phase);
            if (!__any_sync(0xffffffffu, (bad & 0x80008000u) != 0)) break;
            if (++guard > SPIN_LIMIT) { g_err = 3; break; }
            px = ld_rlx4(psrc + ln * 3);
            pm = ld_rlx1(psrc + 128);
          }
          const uint32_t pa = sb + VO_PX + warp * 768 + ln * 4;
          sts1(pa, px.x & 0x7fff7fffu); sts1(pa + 128, px.y & 0x7fff7fffu);
          sts1(pa + 256, px.z & 0x7fff7fffu); sts1(pa + 384, px.w & 0x7fff7fffu);
          sts1(pa + 512, pm & 0x7fff7fffu);
          fence_async_smem();
          if (t < NSEG) TR(3);
        }
        WG_WAIT0();
        float kp[8];
#pragma unroll
        for (int i = 0; i < 8; i++) kp[i] = 0.f;
        if (seg < NSEG) {
          IDS();
          const uint32_t pb = sb + VO_PBR + (seg & 1) * 4096 + wl * 16;
          const uint32_t pb_r = mapa(pb, rank ^ 1), barPB_r = mapa(bars + B_PB + (seg & 1) * 8, rank ^ 1);
          if (wl == 0) mbar_arrive_tx(bars + B_PB + (seg & 1) * 8, 4096);
          GET_D();
          float gv[8];
#pragma unroll
          for (int i = 0; i < 4; i++) {
            kp[2 * i] = rank ? d[4 * i + 2] : d[4 * i]; kp[2 * i + 1] = rank ? d[4 * i + 3] : d[4 * i + 1];
            gv[2 * i] = rank ? d[4 * i] : d[4 * i + 2]; gv[2 * i + 1] = rank ? d[4 * i + 1] : d[4 * i + 3];
          }
          st_async4(pb_r, gv[0], gv[1], gv[2], gv[3], barPB_r);
          st_async4(pb_r + 2048, gv[4], gv[5], gv[6], gv[7], barPB_r);
          XN_RELEASE(0); XN_RELEASE(1);
          TR(13);
        }
        BSYNC(8, 128);
        float o2[16];
#pragma unroll
        for (int i = 0; i < 16; i++) o2[i] = 0.f;
        {
          const int tp = max(t - 1, 0);
          const uint32_t fo_ = (blockIdx.x & 1) * 128;
          const uint64_t ad = mkdesc(sb + VO_VX + (tp & 3) * 12288, 16, 512, 2);
          const uint64_t md = mkdesc(sb + VO_VM + MOD3(tp) * 3072, 0, 128, 0);
          const uint64_t pd = mkdesc(sb + VO_PX, 128, 768, 0);
          WG_FENCE();
          ssA<0, 0, 0>(ad + fo_ * 4, pd); ss32z<0, 0>(o2, ad + 256, pd);
          ssA<0, 0, 1>(ad + fo_ * 4 + 2, pd + 16); ss32<0, 0>(o2, ad + 258, pd + 16);
          ssA<0, 0, 1>(md + fo_, pd + 32); ss32<0, 0>(o2, md + 64, pd + 32);
          WG_COMMIT();
        }
        if (seg < NSEG) {
          IDS();
          const uint32_t pb = sb + VO_PBR + (seg & 1) * 4096 + wl * 16;
          mbar_wait(bars + B_PB + (seg & 1) * 8, (seg >> 1) & 1);
          FIN_VX(4096, rank, pb, true);
          TR(15);
        }
        uint32_t ow[16];
        {
          WAIT_D();
#pragma unroll
          for (int i = 0; i < 8; i++) {
            const int j = (i & 4) * 2 + ((i & 1) << 2) + (i & 2);
            ow[i] = movm(pack_bf16(d[j], d[j + 1]));
            ow[8 + i] = movm(pack_bf16(o2[j], o2[j + 1]));
          }
        }
        if (seg < NSEG) mbar_wait(bars + B_VXR + (seg & 1) * 8, (seg >> 1) & 1);
        fence_async_smem();
        if (t < NSEG) TR(18);
        if (seg < NSEG - 1) {
          const int seg = t + 3;
          VLO(); uint32_t wl_ = ((sb + VO_O4) >> 4) | 0x400000u; LAUNDER(wl_); WG_FENCE();
#pragma unroll
          for (int u = 0; u < 12; u++) { if (u == 0) ssA<1, 1, 0>(dsc(wl_, HI_128), dsc(vl_, HI_64)); else ssA<1, 1, 1>(dsc(wl_ + u * 128, HI_128), dsc(vl_ + u * 64, HI_64)); }
          WG_COMMIT();
        }
        {
          IDS();
          if (ln == 0 && warp < 2 && seg + 1 < NSEG) XN_ISSUE1(VO_XN, seg + 1, warp);
          __syncwarp();
          if (t >= 1) {
            const int tp = t - 1;
            uint4* dst = g_ox4 + ((size_t)((tp >> 2) * 96 + h * 3) * 8 + (tp & 3) * 2) * 128 + wl;
            stg4h(dst + rank * 2048, ow[0], ow[1], ow[2], ow[3]);
            stg4h(dst + rank * 2048 + 128, ow[4], ow[5], ow[6], ow[7]);
            if ((warp >> 1) == rank) {
              stg4h(dst + 1024, ow[8], ow[9], ow[10], ow[11]);
              stg4h(dst + 1024 + 128, ow[12], ow[13], ow[14], ow[15]);
            }
          }
          if (t < NSEG) TR(17);
        }
        WG_WAIT0();
        if (seg < NSEG - 1) {
          const int seg = t + 3;
          IDS();
          STORE_B(4);
          TR(14);
        }
      }
    }
  } else {
    if (tid == 0) GRID_WAIT();
    __syncthreads();
    if (tid == 0) TLM(2);
    mlp1_part(&M.w1, P.b1, sb, (blockIdx.x - 128) >> 1);
  }
  cluster_sync();
  if (tid == 0) TLM(7);
}

typedef CUresult (*EncodeFn)(CUtensorMap*, CUtensorMapDataType, cuuint32_t, void*, const cuuint64_t*, const cuuint64_t*,
                             const cuuint32_t*, const cuuint32_t*, CUtensorMapInterleave, CUtensorMapSwizzle,
                             CUtensorMapL2promotion, CUtensorMapFloatOOBfill);
static void make_map(EncodeFn fn, CUtensorMap* m, const void* p, int K, int N, int nb) {
  cuuint64_t dims[3] = {64, (cuuint64_t)K, (cuuint64_t)(N / 64)};
  cuuint64_t strides[2] = {(cuuint64_t)N * 2, 128};
  cuuint32_t box[3] = {64, 32, (cuuint32_t)nb}, es[3] = {1, 1, 1};
  fn(m, CU_TENSOR_MAP_DATA_TYPE_BFLOAT16, 3, const_cast<void*>(p), dims, strides, box, es, CU_TENSOR_MAP_INTERLEAVE_NONE,
     CU_TENSOR_MAP_SWIZZLE_128B, CU_TENSOR_MAP_L2_PROMOTION_L2_256B, CU_TENSOR_MAP_FLOAT_OOB_FILL_NONE);
}

static void make_map2(EncodeFn fn, CUtensorMap* m, const void* p, int rows, int cols, int bc, int br) {
  cuuint64_t dims[2] = {(cuuint64_t)cols, (cuuint64_t)rows};
  cuuint64_t strides[1] = {(cuuint64_t)cols * 2};
  cuuint32_t box[2] = {(cuuint32_t)bc, (cuuint32_t)br}, es[2] = {1, 1};
  fn(m, CU_TENSOR_MAP_DATA_TYPE_BFLOAT16, 2, const_cast<void*>(p), dims, strides, box, es, CU_TENSOR_MAP_INTERLEAVE_NONE,
     bc == 64 ? CU_TENSOR_MAP_SWIZZLE_128B : CU_TENSOR_MAP_SWIZZLE_64B, CU_TENSOR_MAP_L2_PROMOTION_L2_128B, CU_TENSOR_MAP_FLOAT_OOB_FILL_NONE);
}

extern "C" void kernel_launch(void* const* d_in, const int* in_sizes, int n_in, void* d_out, int out_size) {
  const bf16* x = (const bf16*)d_in[0];
  const bf16* mem0 = (const bf16*)d_in[1];
  const bf16* Wq = (const bf16*)d_in[2];
  const bf16* Wk = (const bf16*)d_in[3];
  const bf16* Wv = (const bf16*)d_in[4];
  const bf16* Wo = (const bf16*)d_in[5];
  const bf16* w1 = (const bf16*)d_in[8];
  const bf16* b1 = (const bf16*)d_in[9];
  const bf16* w2 = (const bf16*)d_in[10];
  const bf16* b2 = (const bf16*)d_in[11];
  bf16* out = (bf16*)d_out;
  cudaStream_t st = cudaStreamPerThread;

  static EncodeFn enc = nullptr;
  if (!enc) {
    cudaFuncSetAttribute(chain_kernel, cudaFuncAttributeMaxDynamicSharedMemorySize, CHAIN_SMEM);
    cudaFuncSetAttribute(final_kernel, cudaFuncAttributeMaxDynamicSharedMemorySize, FIN_SMEM);
    cudaDriverEntryPointQueryResult qr;
    void* f = nullptr;
    cudaGetDriverEntryPoint("cuTensorMapEncodeTiled", &f, cudaEnableDefault, &qr);
    enc = (EncodeFn)f;
  }
  CUtensorMap tmW2, tmWo;
  WMaps M;
  make_map(enc, &M.w1, w1, 640, 1536, 3);
  make_map2(enc, &M.q64, Wq, 640, 6144, 64, 64);
  make_map2(enc, &M.k64, Wk, 640, 6144, 64, 64);
  make_map2(enc, &M.v64, Wv, 640, 6144, 64, 64);
  make_map2(enc, &M.o64, Wo, 6144, 640, 64, 64);
  make_map2(enc, &M.v16, Wv, 640, 6144, 64, 16);
  make_map2(enc, &M.q32, Wq, 640, 6144, 32, 64);
  make_map2(enc, &M.k32, Wk, 640, 6144, 32, 64);
  make_map(enc, &tmW2, w2, 1536, 640, 5);
  make_map(enc, &tmWo, Wo, 6144, 640, 5);
  ChainParams P{Wq, Wk, Wv, Wo, x, mem0, b1};
  chain_kernel<<<132, 384, CHAIN_SMEM, st>>>(M, P);
  cudaLaunchConfig_t cfg = {};
  cfg.gridDim = dim3(128); cfg.blockDim = dim3(384); cfg.dynamicSmemBytes = FIN_SMEM; cfg.stream = st;
  cudaLaunchAttribute at;
  at.id = cudaLaunchAttributeProgrammaticStreamSerialization;
  at.val.programmaticStreamSerializationAllowed = 1;
  cfg.attrs = &at;
  cfg.numAttrs = 1;
  cudaLaunchKernelEx(&cfg, final_kernel, tmWo, tmW2, b2, x, out);
}
```
